```python
import torch

def _softmax(x, axis=-1):
    return torch.softmax(x, dim=axis)

def _gelu(x):
    return torch.nn.functional.gelu(x, approximate='tanh')

def _silu(x):
    return torch.nn.functional.silu(x)

def _sigmoid(x):
    return torch.sigmoid(x)

def _layernorm(x, axis=-1, eps=1e-05):
    m = x.mean(dim=axis, keepdim=True)
    v = x.var(dim=axis, keepdim=True, unbiased=False)
    return (x - m) / torch.sqrt(v + eps)

def _scatter_add(tgt, idx, src, axis=0):
    return tgt.clone().index_add_(axis, idx, src)

def _segment_sum(src, seg, n):
    out = torch.zeros((n,) + src.shape[1:], dtype=src.dtype)
    return out.index_add_(0, seg, src)

def _pad(x, pw):
    flat = tuple((v for pair in reversed(pw) for v in pair))
    return torch.nn.functional.pad(x, flat)
kernel_name = 'adaLN_cond__spectral_gfnet__mixer_token_mlp__prompt'

def setup_inputs():

    _w = lambda a: (lambda t: t.to(torch.bfloat16) if t.is_floating_point() else t)(torch.as_tensor(a))

    def _A_setup():
        B, S, D = (1, 2048, 640)
        Df = D // 2 + 1
        return {'x': _w((lambda *s: torch.randn(*s, dtype=torch.bfloat16) * 0.05)(B, S, D)), 'w_r': _w((lambda *s: torch.randn(*s, dtype=torch.bfloat16) * 1.6)(S, Df) * 0.02), 'w_i': _w((lambda *s: torch.randn(*s, dtype=torch.bfloat16) * 1.6)(S, Df) * 0.02)}
    _A_in = _A_setup()

    def _B_setup():
        B, S, D, F = (1, 2048, 640, 1728)
        return {'x': _w((lambda *s: torch.randn(*s, dtype=torch.bfloat16) * 0.05)(B, S, D)), 'w1': _w((lambda *s: torch.randn(*s, dtype=torch.bfloat16) * 0.8)(S, F) * S ** (-0.5)), 'b1': _w((lambda *s: torch.randn(*s, dtype=torch.bfloat16) * 6.4)(F) * 0.02), 'w2': _w((lambda *s: torch.randn(*s, dtype=torch.bfloat16) * 0.1)(F, S) * F ** (-0.5)), 'b2': _w((lambda *s: torch.randn(*s, dtype=torch.bfloat16) * 0.8)(S) * 0.02)}
    _B_in = _B_setup()
    return {'A_x': _A_in['x'], 'A_w_r': _A_in['w_r'], 'A_w_i': _A_in['w_i'], 'B_x': _B_in['x'], 'B_w1': _B_in['w1'], 'B_b1': _B_in['b1'], 'B_w2': _B_in['w2'], 'B_b2': _B_in['b2'], 'c': _w((lambda *s: torch.randn(*s, dtype=torch.bfloat16) * 0.1)(1, 640) * 8.0), 'w_mod': _w((lambda *s: torch.randn(*s, dtype=torch.bfloat16) * 0.1)(640, 6 * 640) * 640 ** (-0.5) * 8.0)}

def reference(A_x, A_w_r, A_w_i, B_x, B_w1, B_b1, B_w2, B_b2, c, w_mod):

    def _A_ref(x, w_r, w_i):
        B, S, D = x.shape
        X = (lambda x, axes=(-2, -1): torch.fft.rfft2(x.float(), dim=axes))(x, axes=(-2, -1))
        W = w_r + 1j * w_i
        X = X * W
        y = (lambda x, s, axes=(-2, -1): torch.fft.irfft2(x, s=s, dim=axes).to(torch.bfloat16))(X, (S, D), axes=(-2, -1))
        return y

    def _B_ref(x, w1, b1, w2, b2):
        B, S, D = x.shape
        h = _layernorm(x, axis=-1)
        u = torch.einsum('bsd,sf->bdf', h, w1) + b1
        u = _gelu(u)
        y = torch.einsum('bdf,fs->bds', u, w2) + b2
        return (lambda x, *d: x.permute(*d))(y, 0, 2, 1)
    x = A_x
    mod = (_silu(c) @ w_mod).reshape(c.shape[0], 6, 1, -1)
    sa, ca, ga, sb, cb, gb = (mod[:, 0].clone(), mod[:, 1].clone(), mod[:, 2].clone(), mod[:, 3].clone(), mod[:, 4].clone(), mod[:, 5].clone())
    h = _layernorm(x, axis=-1) * (1 + ca) + sa
    x = x + ga * _A_ref(h, A_w_r, A_w_i)
    h = _layernorm(x, axis=-1) * (1 + cb) + sb
    x = x + gb * _B_ref(h, B_w1, B_b1, B_w2, B_b2)
    return x
```

```cpp
#include <cuda_runtime.h>
#include <cuda_bf16.h>
#include <cuda.h>
#include <stdint.h>

namespace {

constexpr int S_ = 2048, D_ = 640, F_ = 1728, DF_ = 321;
constexpr int NT = 320;
constexpr int NCTA = 132;

__device__ float2 g_buf[8 * 128 * 640];
__device__ float2 g_ext[2 * 128];
__device__ __align__(16) __nv_bfloat16 g_mod[6 * 640];
__device__ __align__(1024) __nv_bfloat16 g_x1[S_ * D_];
constexpr int H2P = S_ + 64;
__device__ __align__(1024) __nv_bfloat16 g_h2[D_ * H2P];
__device__ __align__(1024) __nv_bfloat16 g_u[D_ * F_];
__device__ unsigned int g_bar[8];
__device__ __align__(16) unsigned int g_modw[1280];
#define TSTAMP(i)
#define TSTAMPT(i, T)
#define CLK(i)

__device__ __forceinline__ uint32_t smem_u32(const void* p) { return (uint32_t)__cvta_generic_to_shared(p); }
__device__ __forceinline__ float bf16r(float x) { return __bfloat162float(__float2bfloat16_rn(x)); }
__device__ __forceinline__ float bf_lo(uint32_t v) { return __uint_as_float(v << 16); }
__device__ __forceinline__ float bf_hi(uint32_t v) { return __uint_as_float(v & 0xffff0000u); }
__device__ __forceinline__ uint32_t pack_bf16(float lo, float hi) {
    uint32_t r;
    asm("cvt.rn.bf16x2.f32 %0, %1, %2;" : "=r"(r) : "f"(hi), "f"(lo));
    return r;
}
__device__ __forceinline__ float2 cmul(float2 a, float2 b) {
    return make_float2(fmaf(a.x, b.x, -a.y * b.y), fmaf(a.x, b.y, a.y * b.x));
}
__device__ __forceinline__ float2 cmulc(float2 a, float2 b) {
    return make_float2(fmaf(a.x, b.x, a.y * b.y), fmaf(a.y, b.x, -a.x * b.y));
}
__device__ __forceinline__ float2 cadd(float2 a, float2 b) { return make_float2(a.x + b.x, a.y + b.y); }
__device__ __forceinline__ float2 csub(float2 a, float2 b) { return make_float2(a.x - b.x, a.y - b.y); }

template <int DIR>
__device__ __forceinline__ float2 mul_i(float2 a) {
    return DIR > 0 ? make_float2(-a.y, a.x) : make_float2(a.y, -a.x);
}
template <int DIR>
__device__ __forceinline__ void fft4(float2& a0, float2& a1, float2& a2, float2& a3) {
    float2 t0 = cadd(a0, a2), t1 = csub(a0, a2), t2 = cadd(a1, a3), t3 = mul_i<DIR>(csub(a1, a3));
    a0 = cadd(t0, t2); a2 = csub(t0, t2); a1 = cadd(t1, t3); a3 = csub(t1, t3);
}
template <int DIR>
__device__ __forceinline__ float2 mul_w8_1(float2 a) {
    const float c = 0.70710678118654752440f;
    return DIR > 0 ? make_float2((a.x - a.y) * c, (a.x + a.y) * c) : make_float2((a.x + a.y) * c, (a.y - a.x) * c);
}
template <int DIR>
__device__ __forceinline__ float2 mul_w8_3(float2 a) {
    const float c = 0.70710678118654752440f;
    return DIR > 0 ? make_float2(-(a.x + a.y) * c, (a.x - a.y) * c) : make_float2((a.y - a.x) * c, -(a.x + a.y) * c);
}
template <int DIR>
__device__ __forceinline__ float2 mul_cs(float2 a, float c, float s) {
    return DIR > 0 ? make_float2(fmaf(a.x, c, -a.y * s), fmaf(a.y, c, a.x * s))
                   : make_float2(fmaf(a.x, c, a.y * s), fmaf(a.y, c, -a.x * s));
}
template <int DIR>
__device__ __forceinline__ void fft8(float2 (&v)[8]) {
    fft4<DIR>(v[0], v[2], v[4], v[6]);
    fft4<DIR>(v[1], v[3], v[5], v[7]);
    float2 o1 = mul_w8_1<DIR>(v[3]), o2 = mul_i<DIR>(v[5]), o3 = mul_w8_3<DIR>(v[7]), o0 = v[1];
    float2 e0 = v[0], e1 = v[2], e2 = v[4], e3 = v[6];
    v[0] = cadd(e0, o0); v[4] = csub(e0, o0);
    v[1] = cadd(e1, o1); v[5] = csub(e1, o1);
    v[2] = cadd(e2, o2); v[6] = csub(e2, o2);
    v[3] = cadd(e3, o3); v[7] = csub(e3, o3);
}
template <int DIR>
__device__ __forceinline__ void fft16(float2 (&v)[16]) {
    const float c1 = 0.92387953251128675613f, s1 = 0.38268343236508977173f;
#pragma unroll
    for (int n2 = 0; n2 < 4; n2++) fft4<DIR>(v[n2], v[4 + n2], v[8 + n2], v[12 + n2]);
    v[5] = mul_cs<DIR>(v[5], c1, s1);
    v[6] = mul_w8_1<DIR>(v[6]);
    v[7] = mul_cs<DIR>(v[7], s1, c1);
    v[9] = mul_w8_1<DIR>(v[9]);
    v[10] = mul_i<DIR>(v[10]);
    v[11] = mul_w8_3<DIR>(v[11]);
    v[13] = mul_cs<DIR>(v[13], s1, c1);
    v[14] = mul_w8_3<DIR>(v[14]);
    v[15] = mul_cs<DIR>(v[15], -c1, -s1);
#pragma unroll
    for (int k1 = 0; k1 < 4; k1++) fft4<DIR>(v[4 * k1], v[4 * k1 + 1], v[4 * k1 + 2], v[4 * k1 + 3]);
    float2 t;
#define SWP(a, b) t = v[a]; v[a] = v[b]; v[b] = t;
    SWP(1, 4) SWP(2, 8) SWP(3, 12) SWP(6, 9) SWP(7, 13) SWP(11, 14)
#undef SWP
}
template <int DIR>
__device__ __forceinline__ void fft5(float2& x0, float2& x1, float2& x2, float2& x3, float2& x4) {
    const float c1 = 0.30901699437494742410f, c2 = -0.80901699437494742410f;
    const float s1 = 0.95105651629515357212f, s2 = 0.58778525229247312917f;
    float2 t1 = cadd(x1, x4), t2 = cadd(x2, x3), t3 = csub(x1, x4), t4 = csub(x2, x3);
    float2 a1 = make_float2(fmaf(c2, t2.x, fmaf(c1, t1.x, x0.x)), fmaf(c2, t2.y, fmaf(c1, t1.y, x0.y)));
    float2 a2 = make_float2(fmaf(c1, t2.x, fmaf(c2, t1.x, x0.x)), fmaf(c1, t2.y, fmaf(c2, t1.y, x0.y)));
    float2 b1 = make_float2(fmaf(s2, t4.x, s1 * t3.x), fmaf(s2, t4.y, s1 * t3.y));
    float2 b2 = make_float2(fmaf(-s1, t4.x, s2 * t3.x), fmaf(-s1, t4.y, s2 * t3.y));
    x0 = make_float2(x0.x + t1.x + t2.x, x0.y + t1.y + t2.y);
    float2 ib1 = mul_i<DIR>(b1), ib2 = mul_i<DIR>(b2);
    x1 = cadd(a1, ib1); x4 = csub(a1, ib1);
    x2 = cadd(a2, ib2); x3 = csub(a2, ib2);
}
template <int DIR>
__device__ __forceinline__ void fft20(float2 (&v)[20]) {
    float2 t[4][5];
#pragma unroll
    for (int n1 = 0; n1 < 4; n1++)
#pragma unroll
        for (int n2 = 0; n2 < 5; n2++) t[n1][n2] = v[(5 * n1 + 4 * n2) % 20];
#pragma unroll
    for (int n1 = 0; n1 < 4; n1++) fft5<DIR>(t[n1][0], t[n1][1], t[n1][2], t[n1][3], t[n1][4]);
#pragma unroll
    for (int k2 = 0; k2 < 5; k2++) fft4<DIR>(t[0][k2], t[1][k2], t[2][k2], t[3][k2]);
#pragma unroll
    for (int k1 = 0; k1 < 4; k1++)
#pragma unroll
        for (int k2 = 0; k2 < 5; k2++) v[(5 * k1 + 16 * k2) % 20] = t[k1][k2];
}

__device__ __forceinline__ void mbar_init(uint32_t a, uint32_t c) { asm volatile("mbarrier.init.shared::cta.b64 [%0], %1;" ::"r"(a), "r"(c)); }
__device__ __forceinline__ void mbar_expect(uint32_t a, uint32_t b) {
    asm volatile("mbarrier.arrive.expect_tx.shared::cta.b64 _, [%0], %1;" ::"r"(a), "r"(b) : "memory");
}
__device__ __forceinline__ void mbar_arrive(uint32_t a) { asm volatile("mbarrier.arrive.shared::cta.b64 _, [%0];" ::"r"(a) : "memory"); }
__device__ __forceinline__ uint32_t mbar_try(uint32_t a, uint32_t ph) {
    uint32_t ok;
    asm volatile("{\n.reg .pred p;\nmbarrier.try_wait.parity.shared::cta.b64 p, [%1], %2;\nselp.u32 %0, 1, 0, p;\n}"
                 : "=r"(ok) : "r"(a), "r"(ph) : "memory");
    return ok;
}
__device__ __forceinline__ void mbar_wait(uint32_t a, uint32_t ph) {
    if (mbar_try(a, ph)) return;
    int it = 0;
    while (!mbar_try(a, ph)) { if (++it > 4000000) __trap(); }
}
__device__ __forceinline__ uint32_t elect_one() {
    uint32_t pred;
    asm volatile("{\n.reg .pred p;\nelect.sync _|p, 0xffffffff;\nselp.u32 %0, 1, 0, p;\n}" : "=r"(pred));
    return pred;
}
__device__ __forceinline__ void tma2d(uint32_t dst, const CUtensorMap* m, int c0, int c1, uint32_t bar) {
    asm volatile("cp.async.bulk.tensor.2d.shared::cluster.global.mbarrier::complete_tx::bytes [%0], [%1, {%3, %4}], [%2];"
                 ::"r"(dst), "l"(m), "r"(bar), "r"(c0), "r"(c1) : "memory");
}
__device__ __forceinline__ void tma3d(uint32_t dst, const CUtensorMap* m, int c0, int c1, int c2, uint32_t bar) {
    asm volatile("cp.async.bulk.tensor.3d.shared::cluster.global.mbarrier::complete_tx::bytes [%0], [%1, {%3, %4, %5}], [%2];"
                 ::"r"(dst), "l"(m), "r"(bar), "r"(c0), "r"(c1), "r"(c2) : "memory");
}
__device__ __forceinline__ uint64_t make_desc(uint32_t addr, uint32_t lbo, uint32_t sbo) {
    uint64_t d = 0;
    d |= (uint64_t)((addr & 0x3FFFF) >> 4);
    d |= (uint64_t)((lbo >> 4) & 0x3FFF) << 16;
    d |= (uint64_t)((sbo >> 4) & 0x3FFF) << 32;
    d |= (uint64_t)1 << 62;
    return d;
}
#define WG_FENCE() asm volatile("wgmma.fence.sync.aligned;" ::: "memory")
#define WG_COMMIT() asm volatile("wgmma.commit_group.sync.aligned;" ::: "memory")
template <int N>
__device__ __forceinline__ void wg_wait() { asm volatile("wgmma.wait_group.sync.aligned %0;" ::"n"(N) : "memory"); }

__device__ __forceinline__ void wgmma_tn_160(float (&d)[80], uint64_t da, uint64_t db, int scale_d) {
    asm volatile("{\n.reg .pred p;\nsetp.ne.b32 p, %82, 0;\n"
        "wgmma.mma_async.sync.aligned.m64n160k16.f32.bf16.bf16 {%0, %1, %2, %3, %4, %5, %6, %7, %8, %9, %10, %11, %12, %13, %14, %15, %16, %17, %18, %19, %20, %21, %22, %23, %24, %25, %26, %27, %28, %29, %30, %31, %32, %33, %34, %35, %36, %37, %38, %39, %40, %41, %42, %43, %44, %45, %46, %47, %48, %49, %50, %51, %52, %53, %54, %55, %56, %57, %58, %59, %60, %61, %62, %63, %64, %65, %66, %67, %68, %69, %70, %71, %72, %73, %74, %75, %76, %77, %78, %79}, %80, %81, p, 1, 1, 1, 0;\n}\n"
        : "+f"(d[0]), "+f"(d[1]), "+f"(d[2]), "+f"(d[3]), "+f"(d[4]), "+f"(d[5]), "+f"(d[6]), "+f"(d[7]), "+f"(d[8]), "+f"(d[9]), "+f"(d[10]), "+f"(d[11]), "+f"(d[12]), "+f"(d[13]), "+f"(d[14]), "+f"(d[15]), "+f"(d[16]), "+f"(d[17]), "+f"(d[18]), "+f"(d[19]), "+f"(d[20]), "+f"(d[21]), "+f"(d[22]), "+f"(d[23]), "+f"(d[24]), "+f"(d[25]), "+f"(d[26]), "+f"(d[27]), "+f"(d[28]), "+f"(d[29]), "+f"(d[30]), "+f"(d[31]), "+f"(d[32]), "+f"(d[33]), "+f"(d[34]), "+f"(d[35]), "+f"(d[36]), "+f"(d[37]), "+f"(d[38]), "+f"(d[39]), "+f"(d[40]), "+f"(d[41]), "+f"(d[42]), "+f"(d[43]), "+f"(d[44]), "+f"(d[45]), "+f"(d[46]), "+f"(d[47]), "+f"(d[48]), "+f"(d[49]), "+f"(d[50]), "+f"(d[51]), "+f"(d[52]), "+f"(d[53]), "+f"(d[54]), "+f"(d[55]), "+f"(d[56]), "+f"(d[57]), "+f"(d[58]), "+f"(d[59]), "+f"(d[60]), "+f"(d[61]), "+f"(d[62]), "+f"(d[63]), "+f"(d[64]), "+f"(d[65]), "+f"(d[66]), "+f"(d[67]), "+f"(d[68]), "+f"(d[69]), "+f"(d[70]), "+f"(d[71]), "+f"(d[72]), "+f"(d[73]), "+f"(d[74]), "+f"(d[75]), "+f"(d[76]), "+f"(d[77]), "+f"(d[78]), "+f"(d[79])
        : "l"(da), "l"(db), "r"(scale_d));
}

__device__ __forceinline__ void red_release(unsigned int* p) {
    asm volatile("red.release.gpu.global.add.u32 [%0], 1;" ::"l"(p) : "memory");
}
__device__ __forceinline__ unsigned int ld_relaxed(const unsigned int* p) {
    unsigned int v;
    asm volatile("ld.relaxed.gpu.global.u32 %0, [%1];" : "=r"(v) : "l"(p) : "memory");
    return v;
}
__device__ __forceinline__ void spin_until(const unsigned int* p, unsigned int target) {
    int it = 0;
    while (ld_relaxed(p) < target) { if (++it > 20000000) __trap(); }
    unsigned int v;
    asm volatile("ld.acquire.gpu.global.u32 %0, [%1];" : "=r"(v) : "l"(p) : "memory");
}
__device__ __forceinline__ void grid_arrive(int k) {
    __syncthreads();
    if (threadIdx.x == 0) red_release(&g_bar[k]);
}
__device__ __forceinline__ void grid_wait(int k, unsigned int target) {
    if (threadIdx.x == 0) spin_until(&g_bar[k], target);
    __syncthreads();
}

constexpr int SM_STAGE_BYTES = 172032;
constexpr int SM_WF = 90112;
constexpr int SM_WMOD = 131072;
constexpr int G_STAGES = 6, G_STAGE_BYTES = 8192 + 20480;
constexpr int SM_T1 = SM_STAGE_BYTES;
constexpr int SM_T3 = SM_T1 + 5120;
constexpr int SM_T2 = SM_T3 + 5120;
constexpr int SM_TA = SM_T2 + 1024;
constexpr int SM_RED = SM_TA + 1152;
constexpr int SM_SILU = SM_RED + 1280;
constexpr int SM_BARS = SM_SILU + 2560;
constexpr int SM_MODV = SM_BARS + 512;
constexpr int SM_X = SM_MODV + 3840;
constexpr int SM_TOTAL = SM_X + 20480;

struct Params {
    const __nv_bfloat16* x;
    const __nv_bfloat16* w_r;
    const __nv_bfloat16* w_i;
    const __nv_bfloat16* w1;
    const __nv_bfloat16* b1;
    const __nv_bfloat16* w2;
    const __nv_bfloat16* b2;
    const __nv_bfloat16* c;
    const __nv_bfloat16* w_mod;
    __nv_bfloat16* out;
    int stop_after;
};

__device__ __forceinline__ uint32_t badd(uint32_t a, uint32_t b) { uint32_t r; asm("add.rn.bf16x2 %0, %1, %2;" : "=r"(r) : "r"(a), "r"(b)); return r; }
__device__ __forceinline__ uint32_t bsub(uint32_t a, uint32_t b) { uint32_t r; asm("sub.rn.bf16x2 %0, %1, %2;" : "=r"(r) : "r"(a), "r"(b)); return r; }
__device__ __forceinline__ uint32_t bmul(uint32_t a, uint32_t b) { uint32_t r; asm("mul.rn.bf16x2 %0, %1, %2;" : "=r"(r) : "r"(a), "r"(b)); return r; }
__device__ __forceinline__ uint4 ldg128(const void* p) { return __ldg(reinterpret_cast<const uint4*>(p)); }
__device__ __forceinline__ uint4 ldcg128(const void* p) {
    uint4 v;
    asm volatile("ld.global.cg.v4.u32 {%0,%1,%2,%3}, [%4];" : "=r"(v.x), "=r"(v.y), "=r"(v.z), "=r"(v.w) : "l"(p));
    return v;
}
__device__ __forceinline__ void stg128(void* p, uint32_t a, uint32_t b, uint32_t c, uint32_t d) {
    asm volatile("st.global.v4.u32 [%0], {%1,%2,%3,%4};" ::"l"(p), "r"(a), "r"(b), "r"(c), "r"(d) : "memory");
}
__device__ __forceinline__ float2 ldcg64(const float2* p) {
    float2 v;
    asm volatile("ld.global.cg.v2.f32 {%0,%1}, [%2];" : "=f"(v.x), "=f"(v.y) : "l"(p));
    return v;
}

__device__ __forceinline__ void ln_row(uint32_t (&w)[20]) {
    float s0 = 0.f, s1 = 0.f;
#pragma unroll
    for (int i = 0; i < 20; i++) { s0 += bf_lo(w[i]); s1 += bf_hi(w[i]); }
    float s = s0 + s1;
#pragma unroll
    for (int m = 8; m >= 1; m >>= 1) s += __shfl_xor_sync(0xffffffffu, s, m);
    const float mu = s * (1.0f / 640.0f);
    float q0 = 0.f, q1 = 0.f;
#pragma unroll
    for (int i = 0; i < 20; i++) {
        float d0 = bf_lo(w[i]) - mu, d1 = bf_hi(w[i]) - mu;
        q0 = fmaf(d0, d0, q0); q1 = fmaf(d1, d1, q1);
    }
    float q = q0 + q1;
#pragma unroll
    for (int m = 8; m >= 1; m >>= 1) q += __shfl_xor_sync(0xffffffffu, q, m);
    const float var = bf16r(q * (1.0f / 640.0f));
    const float den = bf16r(sqrtf(bf16r(var + 1e-5f)));
    const float r = __fdiv_rn(1.0f, den);
    const uint32_t m2 = pack_bf16(mu, mu);
#pragma unroll
    for (int i = 0; i < 20; i++) {
        const uint32_t d = bsub(w[i], m2);
        w[i] = pack_bf16(bf_lo(d) * r, bf_hi(d) * r);
    }
}
__device__ __forceinline__ void unpack4(uint32_t* w, uint4 v) { w[0] = v.x; w[1] = v.y; w[2] = v.z; w[3] = v.w; }

__device__ __forceinline__ void gemm_consumer(float (&acc)[80], uint32_t sm_base_u, uint32_t fullb, int NK, int tid) {
    const uint32_t emptyb = fullb + 64;
    const uint64_t da0 = make_desc(sm_base_u, 8192, 1024);
    const uint64_t db0 = make_desc(sm_base_u + 8192, 16, 1024);
    uint32_t ph = 0;
    mbar_wait(fullb, 0);
#pragma unroll 1
    for (int kb0 = 0; kb0 < NK; kb0 += G_STAGES) {
#pragma unroll
        for (int s = 0; s < G_STAGES; s++) {
            const int kb = kb0 + s;
            if (kb < NK) {
                constexpr uint64_t one = 1;
                const uint64_t so = one * ((s * G_STAGE_BYTES) >> 4);
                WG_FENCE();
#pragma unroll
                for (int k = 0; k < 4; k++) wgmma_tn_160(acc, da0 + so + k * 128, db0 + so + k * 2, (kb > 0 || k > 0) ? 1 : 0);
                WG_COMMIT();
                const int sn = (s + 1) % G_STAGES;
                if (kb + 1 < NK) mbar_wait(fullb + 8 * sn, (s + 1 == G_STAGES) ? ph ^ 1 : ph);
                wg_wait<1>();
                if (kb > 0 && tid == 0) mbar_arrive(emptyb + 8 * ((s + G_STAGES - 1) % G_STAGES));
            }
        }
        ph ^= 1;
    }
}

__device__ __forceinline__ void load_wmod_slab(const CUtensorMap* tm, uint32_t dst, int cta, uint32_t bar) {
    mbar_expect(bar, 640 * 64);
#pragma unroll
    for (int i = 0; i < 5; i++) tma2d(dst + i * 128 * 64, tm, cta * 32, i * 128, bar);
}
__device__ __forceinline__ void mod_partial(const unsigned char* slab, const float* s_silu, float* s_red, int tid) {
    uint4 wm[8];
#pragma unroll
    for (int i = 0; i < 8; i++) wm[i] = *reinterpret_cast<const uint4*>(slab + ((tid >> 2) + 80 * i) * 64 + (tid & 3) * 16);
    float acc[8];
#pragma unroll
    for (int e = 0; e < 8; e++) acc[e] = 0.f;
#pragma unroll
    for (int i = 0; i < 8; i++) {
        const float sv = s_silu[(tid >> 2) + 80 * i];
        acc[0] = fmaf(sv, bf_lo(wm[i].x), acc[0]); acc[1] = fmaf(sv, bf_hi(wm[i].x), acc[1]);
        acc[2] = fmaf(sv, bf_lo(wm[i].y), acc[2]); acc[3] = fmaf(sv, bf_hi(wm[i].y), acc[3]);
        acc[4] = fmaf(sv, bf_lo(wm[i].z), acc[4]); acc[5] = fmaf(sv, bf_hi(wm[i].z), acc[5]);
        acc[6] = fmaf(sv, bf_lo(wm[i].w), acc[6]); acc[7] = fmaf(sv, bf_hi(wm[i].w), acc[7]);
    }
    const int lane = tid & 31;
    const bool u16 = lane & 16, u8 = lane & 8, u4 = lane & 4;
    float b4[4], b2[2], b1;
#pragma unroll
    for (int e = 0; e < 4; e++) {
        const float keep = u16 ? acc[e + 4] : acc[e], send = u16 ? acc[e] : acc[e + 4];
        b4[e] = keep + __shfl_xor_sync(0xffffffffu, send, 16);
    }
#pragma unroll
    for (int e = 0; e < 2; e++) {
        const float keep = u8 ? b4[e + 2] : b4[e], send = u8 ? b4[e] : b4[e + 2];
        b2[e] = keep + __shfl_xor_sync(0xffffffffu, send, 8);
    }
    {
        const float keep = u4 ? b2[1] : b2[0], send = u4 ? b2[0] : b2[1];
        b1 = keep + __shfl_xor_sync(0xffffffffu, send, 4);
    }
    s_red[(tid >> 5) * 32 + (lane & 3) * 8 + (u16 ? 4 : 0) + (u8 ? 2 : 0) + (u4 ? 1 : 0)] = b1;
}

__device__ __forceinline__ void prefetch_chunk(const void* base, int cta, int half, int tid) {
    if (tid == 288 && cta < 128)
        asm volatile("cp.async.bulk.prefetch.L2.global [%0], %1;" ::"l"((const char*)base + (cta * 2 + half) * 27648), "r"(27648));
}

__global__ void __launch_bounds__(NT, 1)
fused_kernel(const __grid_constant__ CUtensorMap tm_h2, const __grid_constant__ CUtensorMap tm_w1,
             const __grid_constant__ CUtensorMap tm_w2, const __grid_constant__ CUtensorMap tm_u,
             const __grid_constant__ CUtensorMap tm_wm, const __grid_constant__ CUtensorMap tm_x, const Params p) {
    extern __shared__ unsigned char sm_raw[];
    const uint32_t sm_base_u = __shfl_sync(0xffffffffu, (smem_u32(sm_raw) + 1023u) & ~1023u, 0);
    unsigned char* sm = sm_raw + (sm_base_u - smem_u32(sm_raw));
    float2* s_t1 = reinterpret_cast<float2*>(sm + SM_T1);
    float2* s_t3 = reinterpret_cast<float2*>(sm + SM_T3);
    float2* s_t2 = reinterpret_cast<float2*>(sm + SM_T2);
    float2* s_ta = reinterpret_cast<float2*>(sm + SM_TA);
    float* s_red = reinterpret_cast<float*>(sm + SM_RED);
    const uint32_t bars = sm_base_u + SM_BARS;

    const int tid = threadIdx.x, lane = tid & 31;
    const int warp = __shfl_sync(0xffffffffu, tid >> 5, 0);
    const int cta = blockIdx.x;
    const int s0 = cta;
    const int lrow = 2 * warp + (lane >> 4);
    const int ll = lane & 15;
    TSTAMP(0);

    float* s_silu = reinterpret_cast<float*>(sm + SM_SILU);
    const uint32_t bar_x = bars + 256, bar_w = bars + 264;
    if (tid == 288) {
        for (int i = 0; i < 8; i++) { mbar_init(bars + 8 * i, 1); mbar_init(bars + 64 + 8 * i, 1); mbar_init(bars + 128 + 8 * i, 1); mbar_init(bars + 192 + 8 * i, 1); }
        mbar_init(bar_x, 1); mbar_init(bar_w, 1);
        asm volatile("fence.mbarrier_init.release.cluster;" ::: "memory");
        if (cta < 40) load_wmod_slab(&tm_wm, sm_base_u + SM_WMOD, cta, bar_w);
        if (cta == 0) g_bar[4] = 0;
        __nanosleep(400);
        if (cta < 128) {
            mbar_expect(bar_x, 16 * 1280);
#pragma unroll
            for (int i = 0; i < 5; i++) tma3d(sm_base_u + SM_X + i * 4096, &tm_x, i * 128, 0, s0, bar_x);
        }
    }
    uint4 cvv = make_uint4(0, 0, 0, 0);
    if (tid >= 208 && tid < 288) cvv = ldg128(p.c + (tid - 208) * 8);
    uint32_t xw[20];
    TSTAMP(17);
#pragma unroll 1
    for (int i = tid; i < 1552 && tid < 288; i += 288) {
        float ang;
        if (i < 640) ang = (float)((i % 80) * (i / 80)) * (1.0f / 320.0f);
        else if (i < 1280) ang = (float)(((i - 640) & 31) * ((i - 640) >> 5)) * (1.0f / 320.0f);
        else if (i < 1408) ang = (float)(((i - 1280) & 15) * ((i - 1280) >> 4)) * (1.0f / 64.0f);
        else ang = (float)(((128 * ((i - 1408) & 15) + s0) * ((i - 1408) >> 4)) & 2047) * (1.0f / 1024.0f);
        float s, c;
        sincospif(-ang, &s, &c);
        s_t1[i] = make_float2(c, s);
    }
    if (tid >= 208 && tid < 288) {
        const uint32_t w4[4] = {cvv.x, cvv.y, cvv.z, cvv.w};
        float o[8];
#pragma unroll
        for (int e = 0; e < 4; e++) {
            const float c0 = bf_lo(w4[e]), c1 = bf_hi(w4[e]);
            o[2 * e] = bf16r(__fdividef(c0, 1.0f + exp2f(-1.4426950409f * c0)));
            o[2 * e + 1] = bf16r(__fdividef(c1, 1.0f + exp2f(-1.4426950409f * c1)));
        }
        *reinterpret_cast<float4*>(s_silu + (tid - 208) * 8) = make_float4(o[0], o[1], o[2], o[3]);
        *reinterpret_cast<float4*>(s_silu + (tid - 208) * 8 + 4) = make_float4(o[4], o[5], o[6], o[7]);
    }
    TSTAMP(18);
    __syncthreads();
    if (cta < 40) { mbar_wait(bar_w, 0); mod_partial(sm + SM_WMOD, s_silu, s_red, tid); }
    TSTAMP(19);
    __syncthreads();
    TSTAMP(20);
    if (cta < 40 && warp == 9) {
        float t = 0.f;
#pragma unroll
        for (int w = 0; w < 10; w++) t += s_red[w * 32 + lane];
        TSTAMPT(22, 288);
        asm volatile("st.relaxed.gpu.global.u32 [%0], %1;" ::"l"(&g_modw[cta * 32 + lane]), "r"(0x80000000u | (pack_bf16(t, 0.f) & 0xffffu)) : "memory");
        TSTAMPT(23, 288);
    }
    if (tid == 288) {
        const uint32_t cW = 9968;
        const uint32_t off = cta * cW, n = min(cW, 1314816u - min(off, 1314816u));
        if (n) {
            asm volatile("cp.async.bulk.prefetch.L2.global [%0], %1;" ::"l"((const char*)p.w_r + off), "r"(n));
            asm volatile("cp.async.bulk.prefetch.L2.global [%0], %1;" ::"l"((const char*)p.w_i + off), "r"(n));
        }
        if (cta >= 40 && cta < 120) load_wmod_slab(&tm_wm, sm_base_u + SM_WMOD, cta, bar_w);
        asm volatile("prefetch.tensormap [%0];" ::"l"(&tm_h2) : "memory");
        asm volatile("prefetch.tensormap [%0];" ::"l"(&tm_w1) : "memory");
        asm volatile("prefetch.tensormap [%0];" ::"l"(&tm_w2) : "memory");
        asm volatile("prefetch.tensormap [%0];" ::"l"(&tm_u) : "memory");
    }

    if (cta == 128 && tid < 256) {
        const int q = 8 * (tid >> 7), ks = q + 16 * (tid & 127), ksm = (2048 - ks) & 2047;
        reinterpret_cast<float2*>(sm + SM_WF)[tid] =
            make_float2(0.5f * (__bfloat162float(__ldg(p.w_r + ks * DF_ + 320)) + __bfloat162float(__ldg(p.w_r + ksm * DF_ + 320))),
                        0.5f * (__bfloat162float(__ldg(p.w_i + ks * DF_ + 320)) - __bfloat162float(__ldg(p.w_i + ksm * DF_ + 320))));
    }

    if (cta < 128) {
        if (warp < 8) {
            mbar_wait(bar_x, 0);
#pragma unroll
            for (int i = 0; i < 5; i++) unpack4(xw + 4 * i, *reinterpret_cast<const uint4*>(sm + SM_X + i * 4096 + lrow * 256 + ll * 16));
            ln_row(xw);
        }
        TSTAMP(21);
        uint32_t afr[3][4];
        {
            const int g = lane >> 2, t = lane & 3;
            const float scale = 1.0f / (2048.0f * 640.0f);
            float cr[4], ci[4];
#pragma unroll
            for (int i = 0; i < 4; i++) {
                const int j = 2 * t + (i & 1) + (i >> 1) * 8;
                const float2 w = s_ta[g * 16 + j];
                cr[i] = w.x * scale;
                ci[i] = (g == 0 ? ((i & 1) ? -1.0f : 1.0f) : w.y) * scale;
            }
#pragma unroll
            for (int l = 0; l < 3; l++) {
                afr[l][0] = pack_bf16(cr[0], cr[1]);
                afr[l][1] = pack_bf16(ci[0], ci[1]);
                afr[l][2] = pack_bf16(cr[2], cr[3]);
                afr[l][3] = pack_bf16(ci[2], ci[3]);
                cr[0] -= bf_lo(afr[l][0]); cr[1] -= bf_hi(afr[l][0]); ci[0] -= bf_lo(afr[l][1]); ci[1] -= bf_hi(afr[l][1]);
                cr[2] -= bf_lo(afr[l][2]); cr[3] -= bf_hi(afr[l][2]); ci[2] -= bf_lo(afr[l][3]); ci[3] -= bf_hi(afr[l][3]);
            }
        }
        TSTAMP(1);
        if (tid < 160) {
            uint4 a, b;
            int it = 0;
            do {
                asm volatile("ld.relaxed.gpu.global.v4.u32 {%0,%1,%2,%3}, [%4];" : "=r"(a.x), "=r"(a.y), "=r"(a.z), "=r"(a.w) : "l"(g_modw + tid * 8) : "memory");
                asm volatile("ld.relaxed.gpu.global.v4.u32 {%0,%1,%2,%3}, [%4];" : "=r"(b.x), "=r"(b.y), "=r"(b.z), "=r"(b.w) : "l"(g_modw + tid * 8 + 4) : "memory");
                if (++it > 20000000) __trap();
            } while (((a.x & a.y & a.z & a.w & b.x & b.y & b.z & b.w) >> 31) == 0);
            *reinterpret_cast<uint4*>(sm + SM_MODV + tid * 16) =
                make_uint4(__byte_perm(a.x, a.y, 0x5410), __byte_perm(a.z, a.w, 0x5410), __byte_perm(b.x, b.y, 0x5410), __byte_perm(b.z, b.w, 0x5410));
        }
        TSTAMP(2);
        CLK(0);
        prefetch_chunk(p.w1, cta, 0, tid);
        {
            const int r = cta >> 4, b = cta & 15;
            const int q = r ? r : ((b < 8) ? 0 : 8);
            const bool cj = r && b >= 8;
            const int colw = cj ? 601 - 40 * b : 40 * (b & 7);
            const int pp0 = tid / 6, ch = tid - pp0 * 6;
            if (tid < 318) {
#pragma unroll
                for (int it = 0; it < 3; it++) {
                    const int pp = pp0 + 53 * it;
                    if (pp < 128) {
                        const int ks = q + 16 * pp;
                        const int al = ((((cj ? 2048 - ks : ks) * DF_ + colw) * 2) & ~15) + 16 * ch;
                        if (al + 16 <= S_ * DF_ * 2) {
                            asm volatile("cp.async.cg.shared.global [%0], [%1], 16;" ::"r"(sm_base_u + SM_WF + pp * 96 + ch * 16), "l"((const char*)p.w_r + al) : "memory");
                            asm volatile("cp.async.cg.shared.global [%0], [%1], 16;" ::"r"(sm_base_u + SM_WF + 12288 + pp * 96 + ch * 16), "l"((const char*)p.w_i + al) : "memory");
                        }
                    }
                }
            }
            asm volatile("cp.async.commit_group;" ::: "memory");
        }
        __syncthreads();
        if (warp < 8) {
            uint4 sa[5], ca[5];
#pragma unroll
            for (int i = 0; i < 5; i++) {
                sa[i] = *reinterpret_cast<const uint4*>(sm + SM_MODV + (ll + 16 * i) * 16);
                ca[i] = *reinterpret_cast<const uint4*>(sm + SM_MODV + 1280 + (ll + 16 * i) * 16);
            }
            const uint32_t one2 = 0x3f803f80u;
#pragma unroll
            for (int i = 0; i < 5; i++) {
                uint4 h;
                h.x = badd(bmul(xw[4 * i + 0], badd(one2, ca[i].x)), sa[i].x);
                h.y = badd(bmul(xw[4 * i + 1], badd(one2, ca[i].y)), sa[i].y);
                h.z = badd(bmul(xw[4 * i + 2], badd(one2, ca[i].z)), sa[i].z);
                h.w = badd(bmul(xw[4 * i + 3], badd(one2, ca[i].w)), sa[i].w);
                *reinterpret_cast<uint4*>(sm + lrow * 1296 + (ll + 16 * i) * 16) = h;
            }
        }
        CLK(1);
        __syncthreads();
        CLK(2);
        float2* s_f = reinterpret_cast<float2*>(sm + 24576);
        constexpr int PB2 = 24, PK = 121, PR = 968;
        {
            const int g = lane >> 2, t = lane & 3;
            float2 z0[8], z1[8];
            const uint32_t laddr = sm_base_u + (((lane >> 3) & 1) * 8 + (lane & 7)) * 1296 + (80 * (lane >> 4) + 8 * warp) * 2;
#pragma unroll
            for (int ap = 0; ap < 4; ap++) {
                uint32_t b0, b1, b2, b3;
                asm volatile("ldmatrix.sync.aligned.m8n8.x4.trans.shared.b16 {%0,%1,%2,%3}, [%4];"
                             : "=r"(b0), "=r"(b1), "=r"(b2), "=r"(b3) : "r"(laddr + ap * 320));
#pragma unroll
                for (int h = 0; h < 2; h++) {
                    float c0 = 0.f, c1 = 0.f, c2 = 0.f, c3 = 0.f;
                    const uint32_t bb0 = h ? b2 : b0, bb1 = h ? b3 : b1;
#pragma unroll
                    for (int l = 2; l >= 0; l--) {
                        asm volatile("mma.sync.aligned.m16n8k16.row.col.f32.bf16.bf16.f32 {%0,%1,%2,%3}, {%4,%5,%6,%7}, {%8,%9}, {%0,%1,%2,%3};"
                                     : "+f"(c0), "+f"(c1), "+f"(c2), "+f"(c3)
                                     : "r"(afr[l][0]), "r"(afr[l][1]), "r"(afr[l][2]), "r"(afr[l][3]), "r"(bb0), "r"(bb1));
                    }
                    z0[2 * ap + h] = make_float2(c0, c2);
                    z1[2 * ap + h] = make_float2(c1, c3);
                }
            }
            fft8<-1>(z0);
            fft8<-1>(z1);
            const int b = 8 * warp + 2 * t;
            float2* d0 = s_f + g * PR + (b % 5) * PB2 + ((13 * b) & 15);
            float2* d1 = s_f + g * PR + ((b + 1) % 5) * PB2 + ((13 * (b + 1)) & 15);
            d0[0] = z0[0]; d1[0] = z1[0];
#pragma unroll
            for (int k1 = 1; k1 < 8; k1++) {
                const float4 tw = *reinterpret_cast<const float4*>(&s_t1[k1 * 80 + b]);
                d0[k1 * PK] = cmul(z0[k1], make_float2(tw.x, tw.y));
                d1[k1 * PK] = cmul(z1[k1], make_float2(tw.z, tw.w));
            }
        }
        CLK(3);
        __syncthreads();
        CLK(4);
#pragma unroll 1
        for (int i = tid; i < 1024; i += NT) {
            float2* base = s_f + (i >> 7) * PR + ((i >> 4) & 7) * PK + (i & 15);
            float2 v0 = base[0], v1 = base[PB2], v2 = base[2 * PB2], v3 = base[3 * PB2], v4 = base[4 * PB2];
            fft5<-1>(v0, v1, v2, v3, v4);
            base[0] = v0; base[PB2] = v1; base[2 * PB2] = v2; base[3 * PB2] = v3; base[4 * PB2] = v4;
        }
        CLK(5);
        __syncthreads();
        CLK(6);
        {
            const int r = tid / 40, u = tid - r * 40;
            const float2* base = s_f + r * PR + (u & 7) * PK + (u >> 3) * PB2;
            float2 v[16];
#pragma unroll
            for (int b1 = 0; b1 < 16; b1++) v[b1] = base[b1];
            fft16<-1>(v);
            if (r > 0) {
                float2* dst = g_buf + ((size_t)r * 128 + s0) * 640 + u;
#pragma unroll
                for (int c1 = 0; c1 < 16; c1++) dst[c1 * 40] = v[c1];
            } else {
                float2* s_z = reinterpret_cast<float2*>(sm);
                const int m0 = 16 * (u >> 3);
#pragma unroll
                for (int c1 = 0; c1 < 16; c1++) {
                    int m = (65 * c1) % 80 + m0;
                    if (m >= 80) m -= 80;
                    s_z[(u & 7) + 8 * m] = v[c1];
                }
            }
        }
        CLK(7);
        __syncthreads();
        CLK(8);
        {
            const float2* s_z = reinterpret_cast<const float2*>(sm);
            const float2 tw8 = s_ta[8 * 16];
            float2* dst = g_buf + (size_t)s0 * 640;
#pragma unroll 1
            for (int k = tid; k <= 320; k += NT) {
                const float2 a = s_z[k], b = s_z[(640 - k) % 640];
                const float2 T0 = make_float2(0.5f * (a.x + b.x), 0.5f * (a.y - b.y));
                float2 T8 = make_float2(0.5f * (a.y + b.y), -0.5f * (a.x - b.x));
                T8 = cmul(T8, tw8);
                if (k < 320) { dst[k] = T0; dst[320 + k] = T8; }
                else { g_ext[s0] = T0; g_ext[128 + s0] = T8; }
            }
        }
    }
    CLK(9);
    TSTAMP(3);
    grid_arrive(1);
    if (p.stop_after == 1) return;

    {
        const int t = lane >> 2;
        const int il = lane & 3;
        float2* colp = g_buf;
        int stride = 640;
        const bool act = cta < 128 || (cta == 128 && warp == 0);
        bool do_store = true;
        float2 wf[16];
        const int r = cta >> 4, b = cta & 15;
        const int q = r ? r : ((b < 8) ? 0 : 8);
        const bool cj = r && b >= 8;
        const int col0 = cj ? 601 - 40 * b : 40 * (b & 7) + (r ? 0 : 0);
        if (cta < 128) {
            const int u = warp * 4 + il;
            if (r) {
                const int kd = 40 * b + u, m = kd >> 3;
                colp = g_buf + (size_t)r * 128 * 640 + (m & 15) * 40 + (m % 5) * 8 + (kd & 7);
            } else {
                colp = g_buf + 40 * b + u;
            }
        } else if (act) { colp = g_ext + (il & 1) * 128; stride = 1; do_store = il < 2; }
        if (cta >= 40 && cta < 120) {
            mbar_wait(bar_w, 0);
            mod_partial(sm + SM_WMOD, s_silu, s_red, tid);
            __syncthreads();
            if (warp == 9) {
                float tt = 0.f;
#pragma unroll
                for (int w = 0; w < 10; w++) tt += s_red[w * 32 + lane];
                g_mod[cta * 32 + lane] = __float2bfloat16_rn(tt);
            }
        }
        if (cta < 128) {
            asm volatile("cp.async.wait_group 0;" ::: "memory");
            __syncthreads();
            const int colw = r ? col0 : 40 * (b & 7);
            const int u = warp * 4 + il;
            const uint32_t mis = (uint32_t)(((cj ? 2048 - q : q) * DF_ + colw) * 2) & 15u;
            const unsigned char* wp = sm + SM_WF + 2 * t * 96 + mis + 2 * (cj ? 39 - u : u);
            const float sg = cj ? -1.0f : 1.0f;
#pragma unroll
            for (int e = 0; e < 2; e++)
#pragma unroll
                for (int k2 = 0; k2 < 8; k2++) {
                    const int o = (e + 16 * k2) * 96;
                    wf[e * 8 + k2] = make_float2(__bfloat162float(*reinterpret_cast<const __nv_bfloat16*>(wp + o)),
                                                 sg * __bfloat162float(*reinterpret_cast<const __nv_bfloat16*>(wp + 12288 + o)));
                }
            if ((b & 7) == 0 && u == 0) {
                const int kc = cj ? 320 : 0;
                float2 ot[16];
#pragma unroll
                for (int i = 0; i < 16; i++) {
                    const int ks = q + 32 * t + 16 * (i >> 3) + 256 * (i & 7);
                    const int orow = cj ? ks : ((2048 - ks) & 2047);
                    ot[i] = make_float2(__bfloat162float(__ldg(p.w_r + orow * DF_ + kc)), __bfloat162float(__ldg(p.w_i + orow * DF_ + kc)));
                }
#pragma unroll
                for (int i = 0; i < 16; i++) wf[i] = make_float2(0.5f * (wf[i].x + ot[i].x), 0.5f * (wf[i].y - sg * ot[i].y));
            }
        } else if (act) {
            const float2* tab = reinterpret_cast<const float2*>(sm + SM_WF) + (il & 1) * 128 + 2 * t;
#pragma unroll
            for (int i = 0; i < 16; i++) wf[i] = tab[(i >> 3) + 16 * (i & 7)];
        }
        TSTAMP(4);
        grid_wait(1, NCTA);
        TSTAMP(5);
        CLK(10);
        prefetch_chunk(p.w1, cta, 1, tid);
        if (cta < 40 && warp == 9) g_modw[cta * 32 + lane] = 0;
        if (act) {
            float4* s_x = reinterpret_cast<float4*>(sm) + warp * (8 * 36);
            float2 v[16];
            float2* sp = colp + t * stride;
            const int st8 = 8 * stride;
#pragma unroll
            for (int n1 = 0; n1 < 16; n1++) v[n1] = ldcg64(sp + n1 * st8);
            CLK(11);
            fft16<-1>(v);
            CLK(12);
#pragma unroll
            for (int m = 0; m < 8; m++) {
                const float4 tw = *reinterpret_cast<const float4*>(&s_t2[t * 16 + 2 * m]);
                const float2 a = m ? cmul(v[2 * m], make_float2(tw.x, tw.y)) : v[0];
                const float2 b = cmul(v[2 * m + 1], make_float2(tw.z, tw.w));
                s_x[m * 36 + lane] = make_float4(a.x, a.y, b.x, b.y);
            }
            __syncwarp();
            float2 a[8], b[8];
#pragma unroll
            for (int n2 = 0; n2 < 8; n2++) {
                const float4 u = s_x[t * 36 + n2 * 4 + il];
                a[n2] = make_float2(u.x, u.y); b[n2] = make_float2(u.z, u.w);
            }
            fft8<-1>(a);
            fft8<-1>(b);
#pragma unroll
            for (int k2 = 0; k2 < 8; k2++) { a[k2] = cmul(a[k2], wf[k2]); b[k2] = cmul(b[k2], wf[8 + k2]); }
            fft8<1>(a);
            fft8<1>(b);
            __syncwarp();
#pragma unroll
            for (int n2 = 0; n2 < 8; n2++) {
                const float4 tw = *reinterpret_cast<const float4*>(&s_t2[n2 * 16 + 2 * t]);
                const float2 ua = n2 ? cmulc(a[n2], make_float2(tw.x, tw.y)) : a[0];
                const float2 ub = n2 ? cmulc(b[n2], make_float2(tw.z, tw.w)) : b[0];
                s_x[t * 36 + n2 * 4 + il] = make_float4(ua.x, ua.y, ub.x, ub.y);
            }
            __syncwarp();
#pragma unroll
            for (int m = 0; m < 8; m++) {
                const float4 u = s_x[m * 36 + lane];
                v[2 * m] = make_float2(u.x, u.y); v[2 * m + 1] = make_float2(u.z, u.w);
            }
            CLK(13);
            fft16<1>(v);
            CLK(14);
            if (do_store) {
#pragma unroll
                for (int n1 = 0; n1 < 16; n1++) sp[n1 * st8] = v[n1];
            }
        }
    }
    CLK(15);
    TSTAMP(6);
    grid_arrive(2);
    if (p.stop_after == 2) return;

    {
        grid_wait(2, NCTA);
        TSTAMP(7);
        CLK(16);
        prefetch_chunk(p.w2, cta, 0, tid);
        if (cta == 0 && tid == 0) g_bar[1] = 0;
        if (cta < 128) {
            float2* s_a = reinterpret_cast<float2*>(sm);
            constexpr int A_D1 = 33, A_ROW = 20 * 33 + 2;
            float2* s_b = reinterpret_cast<float2*>(sm + 49152);
            constexpr int B_BETA = 16 * 20 + 4, B_ROW = 2 * B_BETA + 8;
            unsigned char* s_y = sm + 98304;
            float2* s_z = reinterpret_cast<float2*>(sm + 126976);
            if (warp >= 8) {
                const float2 tw8 = s_ta[8 * 16];
                const float2* src = g_buf + (size_t)s0 * 640;
                float2 U0[6], U8[6];
                uint4 mv[4];
#pragma unroll
                for (int i = 0; i < 6; i++) {
                    const int k = tid - 256 + 64 * i;
                    const bool in = k < 320;
                    U0[i] = ldcg64(in ? src + k : g_ext + s0);
                    U8[i] = ldcg64(in ? src + 320 + k : g_ext + 128 + s0);
                }
#pragma unroll
                for (int i = 0; i < 4; i++) if (tid - 256 + 64 * i < 240) mv[i] = ldcg128(g_mod + 2 * 640 + (tid - 256 + 64 * i) * 8);
#pragma unroll
                for (int i = 0; i < 6; i++) {
                    const int k = tid - 256 + 64 * i;
                    const float2 a = U0[i], b = cmulc(U8[i], tw8);
                    if (k <= 320) s_z[k] = make_float2(a.x - b.y, a.y + b.x);
                    if (k > 0 && k < 320) s_z[640 - k] = make_float2(a.x + b.y, b.x - a.y);
                }
                asm volatile("bar.sync 2, 96;" ::: "memory");
#pragma unroll
                for (int i = 0; i < 4; i++) if (tid - 256 + 64 * i < 240) *reinterpret_cast<uint4*>(sm + SM_MODV + (tid - 256 + 64 * i) * 16) = mv[i];
            }
            if (warp < 8) {
                const int r = warp, kb = lane;
                float2 v[20];
                if (r > 0) {
                    const float2* src = g_buf + ((size_t)r * 128 + s0) * 640;
                    const int h = kb >> 3;
                    const float2* bj[5];
#pragma unroll
                    for (int j = 0; j < 5; j++) bj[j] = src + h * 40 + ((j + h) % 5) * 8 + (kb & 7);
#pragma unroll
                    for (int ka = 0; ka < 20; ka++) v[ka] = ldcg64(bj[(4 * ka) % 5] + ((4 * ka) & 15) * 40);
                } else {
                    asm volatile("bar.sync 2, 96;" ::: "memory");
#pragma unroll
                    for (int ka = 0; ka < 20; ka++) v[ka] = s_z[32 * ka + kb];
                }
                CLK(17);
                fft20<1>(v);
                CLK(18);
                float2* d = s_a + r * A_ROW + kb;
                d[0] = v[0];
#pragma unroll
                for (int d1 = 1; d1 < 20; d1++) d[d1 * A_D1] = cmulc(v[d1], s_t3[d1 * 32 + kb]);
            }
            CLK(19);
            __syncthreads();
            CLK(20);
            {
                const int r = tid / 40, u = tid - r * 40, beta = u >= 20, d1 = u - 20 * beta;
                const float2* sp = s_a + r * A_ROW + d1 * A_D1 + beta;
                float2 v[16];
#pragma unroll
                for (int al = 0; al < 16; al++) v[al] = sp[2 * al];
                fft16<1>(v);
                float2* dp = s_b + r * B_ROW + beta * B_BETA + d1;
#pragma unroll
                for (int d2 = 0; d2 < 16; d2++) dp[d2 * 20] = v[d2];
            }
            CLK(21);
            __syncthreads();
            CLK(22);
            {
                const float2 w32 = s_t3[10 * 32 + 2 * (tid / 20)];
                float2 Z[16];
#pragma unroll
                for (int r = 0; r < 8; r++) {
                    const float2 v0 = s_b[r * B_ROW + tid];
                    const float2 v1 = cmulc(s_b[r * B_ROW + B_BETA + tid], w32);
                    float2 A = cadd(v0, v1), B = csub(v0, v1);
                    if (r > 0) {
                        const float2 rho = s_ta[r * 16];
                        A = cmulc(A, rho); B = cmulc(B, rho);
                        Z[r] = make_float2(A.x - B.y, A.y + B.x);
                        Z[16 - r] = make_float2(A.x + B.y, B.x - A.y);
                    } else {
                        Z[0] = make_float2(A.x, B.x);
                        Z[8] = make_float2(A.y, B.y);
                    }
                }
                fft16<1>(Z);
                __nv_bfloat16* yp = reinterpret_cast<__nv_bfloat16*>(s_y) + tid;
#pragma unroll
                for (int j = 0; j < 16; j++) {
                    yp[j * 648] = __float2bfloat16_rn(Z[j].x);
                    yp[j * 648 + 320] = __float2bfloat16_rn(Z[j].y);
                }
            }
            CLK(23);
            uint4 ga[5];
            __syncthreads();
            CLK(24);
            if (warp < 8) {
                const size_t rowoff = (size_t)(128 * lrow + s0) * D_;
                const uint32_t one2 = 0x3f803f80u;
#pragma unroll
                for (int i = 0; i < 5; i++) {
                    ga[i] = *reinterpret_cast<const uint4*>(sm + SM_MODV + (ll + 16 * i) * 16);
                }
#pragma unroll
                for (int i = 0; i < 5; i++) {
                    const uint4 y = *reinterpret_cast<const uint4*>(s_y + lrow * 1296 + (ll + 16 * i) * 16);
                    unpack4(xw + 4 * i, *reinterpret_cast<const uint4*>(sm + SM_X + i * 4096 + lrow * 256 + ll * 16));
                    xw[4 * i + 0] = badd(xw[4 * i + 0], bmul(ga[i].x, y.x));
                    xw[4 * i + 1] = badd(xw[4 * i + 1], bmul(ga[i].y, y.y));
                    xw[4 * i + 2] = badd(xw[4 * i + 2], bmul(ga[i].z, y.z));
                    xw[4 * i + 3] = badd(xw[4 * i + 3], bmul(ga[i].w, y.w));
                    stg128(g_x1 + rowoff + (ll + 16 * i) * 8, xw[4 * i], xw[4 * i + 1], xw[4 * i + 2], xw[4 * i + 3]);
                }
                CLK(25);
#pragma unroll 1
                for (int it = 0; it < 2; it++) {
                    ln_row(xw);
                    if (it == 0) {
#pragma unroll
                        for (int i = 0; i < 5; i++) {
                            const uint4 sb = *reinterpret_cast<const uint4*>(sm + SM_MODV + 1280 + (ll + 16 * i) * 16);
                            const uint4 cb = *reinterpret_cast<const uint4*>(sm + SM_MODV + 2560 + (ll + 16 * i) * 16);
                            xw[4 * i + 0] = badd(bmul(xw[4 * i + 0], badd(one2, cb.x)), sb.x);
                            xw[4 * i + 1] = badd(bmul(xw[4 * i + 1], badd(one2, cb.y)), sb.y);
                            xw[4 * i + 2] = badd(bmul(xw[4 * i + 2], badd(one2, cb.z)), sb.z);
                            xw[4 * i + 3] = badd(bmul(xw[4 * i + 3], badd(one2, cb.w)), sb.w);
                        }
                    }
                }
                CLK(26);
#pragma unroll
                for (int i = 0; i < 5; i++)
                    *reinterpret_cast<uint4*>(sm + lrow * 1296 + (ll + 16 * i) * 16) = make_uint4(xw[4 * i], xw[4 * i + 1], xw[4 * i + 2], xw[4 * i + 3]);
            }
            CLK(27);
            __syncthreads();
            CLK(28);
            {
#pragma unroll
                for (int it = 0; it < 2; it++) {
                    const int dp = (tid >> 1) + 160 * it, h = tid & 1;
                    uint32_t w[8];
#pragma unroll
                    for (int j = 0; j < 8; j++) w[j] = *reinterpret_cast<const uint32_t*>(sm + (8 * h + j) * 1296 + dp * 4);
                    stg128(g_h2 + (size_t)(2 * dp) * H2P + 16 * s0 + 8 * h,
                           __byte_perm(w[0], w[1], 0x5410), __byte_perm(w[2], w[3], 0x5410), __byte_perm(w[4], w[5], 0x5410), __byte_perm(w[6], w[7], 0x5410));
                    stg128(g_h2 + (size_t)(2 * dp + 1) * H2P + 16 * s0 + 8 * h,
                           __byte_perm(w[0], w[1], 0x7632), __byte_perm(w[2], w[3], 0x7632), __byte_perm(w[4], w[5], 0x7632), __byte_perm(w[6], w[7], 0x7632));
                }
            }
        }
    }
    CLK(29);
    TSTAMP(8);
    asm volatile("fence.proxy.async.shared::cta;" ::: "memory");
    grid_arrive(3);
    if (p.stop_after == 3) return;

#pragma unroll 1
    for (int g = 0; g < 2; g++) {
        grid_wait(3 + g, NCTA);
        TSTAMP(9 + 2 * g);
        CLK(36 + g);
        if (g == 0) prefetch_chunk(p.w2, cta, 1, tid);
        if (cta == 0 && tid == 0) g_bar[2 + g] = 0;
        if (cta < (g ? 128 : 108)) {
            const int mt = cta >> 2, nt = cta & 3;
            const uint32_t fullb = bars + 128 * g, emptyb = fullb + 64;
            const int NK = g ? 27 : 32;
            float* s_c = reinterpret_cast<float*>(sm);
            uint4 bb = make_uint4(0, 0, 0, 0);
            if (g == 0) bb = ldg128(p.b1 + mt * 64 + (tid & 7) * 8);
            else if (warp >= 5) {
                const int t5 = tid - 160;
#pragma unroll
                for (int it = 0; it < 8; it++) {
                    const int i = t5 + it * 160, row = i / 20, c8 = i - row * 20;
                    *reinterpret_cast<uint4*>(sm + SM_X + i * 16) = ldcg128(g_x1 + (size_t)(mt * 64 + row) * D_ + nt * 160 + c8 * 8);
                }
                if (t5 < 20) *reinterpret_cast<uint4*>(sm + SM_MODV + t5 * 16) = ldcg128(g_mod + 5 * 640 + nt * 160 + t5 * 8);
                else if (t5 < 28) *reinterpret_cast<uint4*>(sm + SM_MODV + 320 + (t5 - 20) * 16) = ldg128(p.b2 + mt * 64 + (t5 - 20) * 8);
            }
            if (warp == 4) {
                const CUtensorMap* ta = g ? &tm_w2 : &tm_w1;
                const CUtensorMap* tb = g ? &tm_u : &tm_h2;
                int s = 0; uint32_t ph = 1;
                asm volatile("fence.proxy.async.global;" ::: "memory");
#pragma unroll 1
                for (int kb = 0; kb < NK; kb++) {
                    mbar_wait(emptyb + 8 * s, ph);
                    if (elect_one()) {
                        const uint32_t sa = sm_base_u + s * G_STAGE_BYTES;
                        mbar_expect(fullb + 8 * s, G_STAGE_BYTES);
                        if (g) tma2d(sa, ta, mt * 64, kb * 64, fullb + 8 * s);
                        else tma3d(sa, ta, mt * 64, 0, kb * 4, fullb + 8 * s);
                        tma2d(sa + 8192, tb, kb * 64, nt * 160, fullb + 8 * s);
                    }
                    if (++s == G_STAGES) { s = 0; ph ^= 1; }
                }
            } else if (warp < 4) {
                float acc[80];
                gemm_consumer(acc, sm_base_u, fullb, NK, tid);
                wg_wait<0>();
                CLK(31 + 2 * g);
                TSTAMP(14 + 2 * g);
                asm volatile("bar.sync 1, 128;" ::: "memory");
                CLK(44 + 4 * g);
                if (g == 0) {
                    float* cp = s_c + (2 * (lane & 3)) * 68 + warp * 16 + (lane >> 2);
#pragma unroll
                    for (int i = 0; i < 20; i++) {
                        cp[(i * 8) * 68] = acc[i * 4]; cp[(i * 8 + 1) * 68] = acc[i * 4 + 1];
                        cp[(i * 8) * 68 + 8] = acc[i * 4 + 2]; cp[(i * 8 + 1) * 68 + 8] = acc[i * 4 + 3];
                    }
                } else {
                    float* cp = s_c + (warp * 16 + (lane >> 2)) * 168 + 2 * (lane & 3);
#pragma unroll
                    for (int i = 0; i < 20; i++) {
                        *reinterpret_cast<float2*>(cp + i * 8) = make_float2(acc[i * 4], acc[i * 4 + 1]);
                        *reinterpret_cast<float2*>(cp + 8 * 168 + i * 8) = make_float2(acc[i * 4 + 2], acc[i * 4 + 3]);
                    }
                }
            }
#pragma unroll 1
            for (int pass = (warp >= 5 ? 0 : 1); pass < 2; pass++) {
                if (pass) { CLK(45 + 4 * g); __syncthreads(); CLK(46 + 4 * g); }
                if (g == 0) {
#pragma unroll 1
                    for (int d = tid >> 3; d < (pass ? 160 : 40); d += NT / 8) {
                        const float4 a0 = *reinterpret_cast<const float4*>(s_c + d * 68 + (tid & 7) * 8);
                        const float4 a1 = *reinterpret_cast<const float4*>(s_c + d * 68 + (tid & 7) * 8 + 4);
                        uint32_t u[4] = {badd(pack_bf16(a0.x, a0.y), bb.x), badd(pack_bf16(a0.z, a0.w), bb.y),
                                         badd(pack_bf16(a1.x, a1.y), bb.z), badd(pack_bf16(a1.z, a1.w), bb.w)};
#pragma unroll
                        for (int e = 0; e < 4; e++) {
                            const float x0 = bf_lo(u[e]), x1 = bf_hi(u[e]);
                            const float e0 = exp2f(x0 * fmaf(x0 * x0, -0.1029432397f, -2.3022081985f));
                            const float e1 = exp2f(x1 * fmaf(x1 * x1, -0.1029432397f, -2.3022081985f));
                            u[e] = pack_bf16(__fdividef(x0, 1.0f + e0), __fdividef(x1, 1.0f + e1));
                        }
                        if (pass) stg128(g_u + (size_t)(nt * 160 + d) * F_ + mt * 64 + (tid & 7) * 8, u[0], u[1], u[2], u[3]);
                        else if (u[0] == 0x7fc1beefu && u[1] == u[2] && u[3] == 0x12345u) g_bar[7] = 1;
                    }
                } else {
#pragma unroll 1
                    for (int i = tid; i < (pass ? 64 * 20 : NT); i += NT) {
                        const int row = i / 20, c8 = i - row * 20;
                        const uint4 xv = *reinterpret_cast<const uint4*>(sm + SM_X + i * 16);
                        const uint4 gb = *reinterpret_cast<const uint4*>(sm + SM_MODV + c8 * 16);
                        const uint32_t b2 = *reinterpret_cast<const unsigned short*>(sm + SM_MODV + 320 + row * 2);
                        const uint32_t b22 = b2 | (b2 << 16);
                        const float4 a0 = *reinterpret_cast<const float4*>(s_c + row * 168 + c8 * 8);
                        const float4 a1 = *reinterpret_cast<const float4*>(s_c + row * 168 + c8 * 8 + 4);
                        const uint32_t o0 = badd(xv.x, bmul(gb.x, badd(pack_bf16(a0.x, a0.y), b22)));
                        const uint32_t o1 = badd(xv.y, bmul(gb.y, badd(pack_bf16(a0.z, a0.w), b22)));
                        const uint32_t o2 = badd(xv.z, bmul(gb.z, badd(pack_bf16(a1.x, a1.y), b22)));
                        const uint32_t o3 = badd(xv.w, bmul(gb.w, badd(pack_bf16(a1.z, a1.w), b22)));
                        if (pass) stg128(p.out + (size_t)(mt * 64 + row) * D_ + nt * 160 + c8 * 8, o0, o1, o2, o3);
                        else if (o0 == 0x7fc1beefu && o1 == o2 && o3 == 0x12345u) g_bar[7] = 1;
                    }
                }
            }
        }
        CLK(34 + g);
        TSTAMP(10 + 2 * g);
        if (g == 0) {
            asm volatile("fence.proxy.async.shared::cta;" ::: "memory");
            grid_arrive(4);
            if (p.stop_after == 4) return;
        }
    }
}

typedef CUresult (*EncodeFn)(CUtensorMap*, CUtensorMapDataType, cuuint32_t, void*, const cuuint64_t*, const cuuint64_t*,
                             const cuuint32_t*, const cuuint32_t*, CUtensorMapInterleave, CUtensorMapSwizzle,
                             CUtensorMapL2promotion, CUtensorMapFloatOOBfill);

CUtensorMap make_map(EncodeFn enc, void* ptr, int rank, const cuuint64_t* dims, const cuuint64_t* strides_bytes, const cuuint32_t* box,
                     CUtensorMapSwizzle swz = CU_TENSOR_MAP_SWIZZLE_128B) {
    CUtensorMap m;
    cuuint32_t es[3] = {1, 1, 1};
    enc(&m, CU_TENSOR_MAP_DATA_TYPE_BFLOAT16, rank, ptr, dims, strides_bytes, box, es, CU_TENSOR_MAP_INTERLEAVE_NONE,
        swz, CU_TENSOR_MAP_L2_PROMOTION_L2_128B, CU_TENSOR_MAP_FLOAT_OOB_FILL_NONE);
    return m;
}

}

int g_debug_stop_after = 0;

extern "C" void kernel_launch(void* const* d_in, const int* in_sizes, int n_in, void* d_out, int out_size) {
    (void)in_sizes; (void)n_in; (void)out_size;
    static EncodeFn enc = nullptr;
    static void *p_h2 = nullptr, *p_u = nullptr;
    if (!enc) {
        void* fn = nullptr;
        cudaDriverEntryPointQueryResult qr;
        cudaGetDriverEntryPoint("cuTensorMapEncodeTiled", &fn, cudaEnableDefault, &qr);
        enc = (EncodeFn)fn;
        cudaGetSymbolAddress(&p_h2, g_h2);
        cudaGetSymbolAddress(&p_u, g_u);
        cudaFuncSetAttribute(fused_kernel, cudaFuncAttributeMaxDynamicSharedMemorySize, SM_TOTAL + 1024);
    }
    Params p;
    p.x = (const __nv_bfloat16*)d_in[0];
    p.w_r = (const __nv_bfloat16*)d_in[1];
    p.w_i = (const __nv_bfloat16*)d_in[2];
    p.w1 = (const __nv_bfloat16*)d_in[4];
    p.b1 = (const __nv_bfloat16*)d_in[5];
    p.w2 = (const __nv_bfloat16*)d_in[6];
    p.b2 = (const __nv_bfloat16*)d_in[7];
    p.c = (const __nv_bfloat16*)d_in[8];
    p.w_mod = (const __nv_bfloat16*)d_in[9];
    p.out = (__nv_bfloat16*)d_out;
    p.stop_after = g_debug_stop_after;

    CUtensorMap tm_h2, tm_w1, tm_w2, tm_u, tm_wm, tm_x;
    {
        cuuint64_t dims[2] = {2048, 640}, str[1] = {H2P * 2};
        cuuint32_t box[2] = {64, 160};
        tm_h2 = make_map(enc, p_h2, 2, dims, str, box);
    }
    {
        cuuint64_t dims[3] = {1728, 16, 128}, str[2] = {(cuuint64_t)128 * 1728 * 2, 1728 * 2};
        cuuint32_t box[3] = {64, 16, 4};
        tm_w1 = make_map(enc, (void*)p.w1, 3, dims, str, box);
    }
    {
        cuuint64_t dims[2] = {2048, 1728}, str[1] = {2048 * 2};
        cuuint32_t box[2] = {64, 64};
        tm_w2 = make_map(enc, (void*)p.w2, 2, dims, str, box);
    }
    {
        cuuint64_t dims[2] = {1728, 640}, str[1] = {1728 * 2};
        cuuint32_t box[2] = {64, 160};
        tm_u = make_map(enc, p_u, 2, dims, str, box);
    }
    {
        cuuint64_t dims[2] = {3840, 640}, str[1] = {3840 * 2};
        cuuint32_t box[2] = {32, 128};
        tm_wm = make_map(enc, (void*)p.w_mod, 2, dims, str, box, CU_TENSOR_MAP_SWIZZLE_NONE);
    }
    {
        cuuint64_t dims[3] = {640, 16, 128}, str[2] = {(cuuint64_t)128 * 640 * 2, 640 * 2};
        cuuint32_t box[3] = {128, 16, 1};
        tm_x = make_map(enc, (void*)p.x, 3, dims, str, box, CU_TENSOR_MAP_SWIZZLE_NONE);
    }
    fused_kernel<<<NCTA, NT, SM_TOTAL + 1024, cudaStreamPerThread>>>(tm_h2, tm_w1, tm_w2, tm_u, tm_wm, tm_x, p);
}
```

```cpp
#include <cuda_runtime.h>
#include <cuda_bf16.h>
#include <cuda.h>
#include <stdint.h>

namespace {

constexpr int S_ = 2048, D_ = 640, F_ = 1728, DF_ = 321;
constexpr int NT = 320;
constexpr int NCTA = 132;

__device__ float2 g_buf[8 * 128 * 640];
__device__ float2 g_ext[2 * 128];
__device__ __align__(16) __nv_bfloat16 g_mod[6 * 640];
__device__ __align__(1024) __nv_bfloat16 g_x1[S_ * D_];
constexpr int H2P = S_ + 64;
__device__ __align__(1024) __nv_bfloat16 g_h2[D_ * H2P];
__device__ __align__(1024) __nv_bfloat16 g_u[D_ * F_];
__device__ unsigned int g_bar[8];
__device__ __align__(16) unsigned int g_modw[1280];
#define DBG_STOP(n)
#define TSTAMP(i)
#define TSTAMPT(i, T)
#define CLK(i)

__device__ __forceinline__ uint32_t smem_u32(const void* p) { return (uint32_t)__cvta_generic_to_shared(p); }
__device__ __forceinline__ float bf16r(float x) { return __bfloat162float(__float2bfloat16_rn(x)); }
__device__ __forceinline__ float bf_lo(uint32_t v) { return __uint_as_float(v << 16); }
__device__ __forceinline__ float bf_hi(uint32_t v) { return __uint_as_float(v & 0xffff0000u); }
__device__ __forceinline__ uint32_t pack_bf16(float lo, float hi) {
    uint32_t r;
    asm("cvt.rn.bf16x2.f32 %0, %1, %2;" : "=r"(r) : "f"(hi), "f"(lo));
    return r;
}
__device__ __forceinline__ float2 cmul(float2 a, float2 b) {
    return make_float2(fmaf(a.x, b.x, -a.y * b.y), fmaf(a.x, b.y, a.y * b.x));
}
__device__ __forceinline__ float2 cmulc(float2 a, float2 b) {
    return make_float2(fmaf(a.x, b.x, a.y * b.y), fmaf(a.y, b.x, -a.x * b.y));
}
__device__ __forceinline__ float2 cadd(float2 a, float2 b) { return make_float2(a.x + b.x, a.y + b.y); }
__device__ __forceinline__ float2 csub(float2 a, float2 b) { return make_float2(a.x - b.x, a.y - b.y); }

template <int DIR>
__device__ __forceinline__ float2 mul_i(float2 a) {
    return DIR > 0 ? make_float2(-a.y, a.x) : make_float2(a.y, -a.x);
}
template <int DIR>
__device__ __forceinline__ void fft4(float2& a0, float2& a1, float2& a2, float2& a3) {
    float2 t0 = cadd(a0, a2), t1 = csub(a0, a2), t2 = cadd(a1, a3), t3 = mul_i<DIR>(csub(a1, a3));
    a0 = cadd(t0, t2); a2 = csub(t0, t2); a1 = cadd(t1, t3); a3 = csub(t1, t3);
}
template <int DIR>
__device__ __forceinline__ float2 mul_w8_1(float2 a) {
    const float c = 0.70710678118654752440f;
    return DIR > 0 ? make_float2((a.x - a.y) * c, (a.x + a.y) * c) : make_float2((a.x + a.y) * c, (a.y - a.x) * c);
}
template <int DIR>
__device__ __forceinline__ float2 mul_w8_3(float2 a) {
    const float c = 0.70710678118654752440f;
    return DIR > 0 ? make_float2(-(a.x + a.y) * c, (a.x - a.y) * c) : make_float2((a.y - a.x) * c, -(a.x + a.y) * c);
}
template <int DIR>
__device__ __forceinline__ float2 mul_cs(float2 a, float c, float s) {
    return DIR > 0 ? make_float2(fmaf(a.x, c, -a.y * s), fmaf(a.y, c, a.x * s))
                   : make_float2(fmaf(a.x, c, a.y * s), fmaf(a.y, c, -a.x * s));
}
template <int DIR>
__device__ __forceinline__ void fft8(float2 (&v)[8]) {
    fft4<DIR>(v[0], v[2], v[4], v[6]);
    fft4<DIR>(v[1], v[3], v[5], v[7]);
    float2 o1 = mul_w8_1<DIR>(v[3]), o2 = mul_i<DIR>(v[5]), o3 = mul_w8_3<DIR>(v[7]), o0 = v[1];
    float2 e0 = v[0], e1 = v[2], e2 = v[4], e3 = v[6];
    v[0] = cadd(e0, o0); v[4] = csub(e0, o0);
    v[1] = cadd(e1, o1); v[5] = csub(e1, o1);
    v[2] = cadd(e2, o2); v[6] = csub(e2, o2);
    v[3] = cadd(e3, o3); v[7] = csub(e3, o3);
}
template <int DIR>
__device__ __forceinline__ void fft16(float2 (&v)[16]) {
    const float c1 = 0.92387953251128675613f, s1 = 0.38268343236508977173f;
#pragma unroll
    for (int n2 = 0; n2 < 4; n2++) fft4<DIR>(v[n2], v[4 + n2], v[8 + n2], v[12 + n2]);
    v[5] = mul_cs<DIR>(v[5], c1, s1);
    v[6] = mul_w8_1<DIR>(v[6]);
    v[7] = mul_cs<DIR>(v[7], s1, c1);
    v[9] = mul_w8_1<DIR>(v[9]);
    v[10] = mul_i<DIR>(v[10]);
    v[11] = mul_w8_3<DIR>(v[11]);
    v[13] = mul_cs<DIR>(v[13], s1, c1);
    v[14] = mul_w8_3<DIR>(v[14]);
    v[15] = mul_cs<DIR>(v[15], -c1, -s1);
#pragma unroll
    for (int k1 = 0; k1 < 4; k1++) fft4<DIR>(v[4 * k1], v[4 * k1 + 1], v[4 * k1 + 2], v[4 * k1 + 3]);
    float2 t;
#define SWP(a, b) t = v[a]; v[a] = v[b]; v[b] = t;
    SWP(1, 4) SWP(2, 8) SWP(3, 12) SWP(6, 9) SWP(7, 13) SWP(11, 14)
#undef SWP
}
template <int DIR>
__device__ __forceinline__ void fft5(float2& x0, float2& x1, float2& x2, float2& x3, float2& x4) {
    const float c1 = 0.30901699437494742410f, c2 = -0.80901699437494742410f;
    const float s1 = 0.95105651629515357212f, s2 = 0.58778525229247312917f;
    float2 t1 = cadd(x1, x4), t2 = cadd(x2, x3), t3 = csub(x1, x4), t4 = csub(x2, x3);
    float2 a1 = make_float2(fmaf(c2, t2.x, fmaf(c1, t1.x, x0.x)), fmaf(c2, t2.y, fmaf(c1, t1.y, x0.y)));
    float2 a2 = make_float2(fmaf(c1, t2.x, fmaf(c2, t1.x, x0.x)), fmaf(c1, t2.y, fmaf(c2, t1.y, x0.y)));
    float2 b1 = make_float2(fmaf(s2, t4.x, s1 * t3.x), fmaf(s2, t4.y, s1 * t3.y));
    float2 b2 = make_float2(fmaf(-s1, t4.x, s2 * t3.x), fmaf(-s1, t4.y, s2 * t3.y));
    x0 = make_float2(x0.x + t1.x + t2.x, x0.y + t1.y + t2.y);
    float2 ib1 = mul_i<DIR>(b1), ib2 = mul_i<DIR>(b2);
    x1 = cadd(a1, ib1); x4 = csub(a1, ib1);
    x2 = cadd(a2, ib2); x3 = csub(a2, ib2);
}
template <int DIR>
__device__ __forceinline__ void fft20(float2 (&v)[20]) {
    float2 t[4][5];
#pragma unroll
    for (int n1 = 0; n1 < 4; n1++)
#pragma unroll
        for (int n2 = 0; n2 < 5; n2++) t[n1][n2] = v[(5 * n1 + 4 * n2) % 20];
#pragma unroll
    for (int n1 = 0; n1 < 4; n1++) fft5<DIR>(t[n1][0], t[n1][1], t[n1][2], t[n1][3], t[n1][4]);
#pragma unroll
    for (int k2 = 0; k2 < 5; k2++) fft4<DIR>(t[0][k2], t[1][k2], t[2][k2], t[3][k2]);
#pragma unroll
    for (int k1 = 0; k1 < 4; k1++)
#pragma unroll
        for (int k2 = 0; k2 < 5; k2++) v[(5 * k1 + 16 * k2) % 20] = t[k1][k2];
}

__device__ __forceinline__ void mbar_init(uint32_t a, uint32_t c) { asm volatile("mbarrier.init.shared::cta.b64 [%0], %1;" ::"r"(a), "r"(c)); }
__device__ __forceinline__ void mbar_expect(uint32_t a, uint32_t b) {
    asm volatile("mbarrier.arrive.expect_tx.shared::cta.b64 _, [%0], %1;" ::"r"(a), "r"(b) : "memory");
}
__device__ __forceinline__ void mbar_arrive(uint32_t a) { asm volatile("mbarrier.arrive.shared::cta.b64 _, [%0];" ::"r"(a) : "memory"); }
__device__ __forceinline__ uint32_t mbar_try(uint32_t a, uint32_t ph) {
    uint32_t ok;
    asm volatile("{\n.reg .pred p;\nmbarrier.try_wait.parity.shared::cta.b64 p, [%1], %2;\nselp.u32 %0, 1, 0, p;\n}"
                 : "=r"(ok) : "r"(a), "r"(ph) : "memory");
    return ok;
}
__device__ __forceinline__ void mbar_wait(uint32_t a, uint32_t ph) {
    if (mbar_try(a, ph)) return;
    int it = 0;
    while (!mbar_try(a, ph)) { if (++it > 4000000) __trap(); }
}
__device__ __forceinline__ uint32_t elect_one() {
    uint32_t pred;
    asm volatile("{\n.reg .pred p;\nelect.sync _|p, 0xffffffff;\nselp.u32 %0, 1, 0, p;\n}" : "=r"(pred));
    return pred;
}
__device__ __forceinline__ void tma2d(uint32_t dst, const CUtensorMap* m, int c0, int c1, uint32_t bar) {
    asm volatile("cp.async.bulk.tensor.2d.shared::cluster.global.mbarrier::complete_tx::bytes [%0], [%1, {%3, %4}], [%2];"
                 ::"r"(dst), "l"(m), "r"(bar), "r"(c0), "r"(c1) : "memory");
}
__device__ __forceinline__ void tma3d(uint32_t dst, const CUtensorMap* m, int c0, int c1, int c2, uint32_t bar) {
    asm volatile("cp.async.bulk.tensor.3d.shared::cluster.global.mbarrier::complete_tx::bytes [%0], [%1, {%3, %4, %5}], [%2];"
                 ::"r"(dst), "l"(m), "r"(bar), "r"(c0), "r"(c1), "r"(c2) : "memory");
}
__device__ __forceinline__ uint64_t make_desc(uint32_t addr, uint32_t lbo, uint32_t sbo) {
    uint64_t d = 0;
    d |= (uint64_t)((addr & 0x3FFFF) >> 4);
    d |= (uint64_t)((lbo >> 4) & 0x3FFF) << 16;
    d |= (uint64_t)((sbo >> 4) & 0x3FFF) << 32;
    d |= (uint64_t)1 << 62;
    return d;
}
#define WG_FENCE() asm volatile("wgmma.fence.sync.aligned;" ::: "memory")
#define WG_COMMIT() asm volatile("wgmma.commit_group.sync.aligned;" ::: "memory")
template <int N>
__device__ __forceinline__ void wg_wait() { asm volatile("wgmma.wait_group.sync.aligned %0;" ::"n"(N) : "memory"); }

__device__ __forceinline__ void wgmma_tn_160(float (&d)[80], uint64_t da, uint64_t db, int scale_d) {
    asm volatile("{\n.reg .pred p;\nsetp.ne.b32 p, %82, 0;\n"
        "wgmma.mma_async.sync.aligned.m64n160k16.f32.bf16.bf16 {%0, %1, %2, %3, %4, %5, %6, %7, %8, %9, %10, %11, %12, %13, %14, %15, %16, %17, %18, %19, %20, %21, %22, %23, %24, %25, %26, %27, %28, %29, %30, %31, %32, %33, %34, %35, %36, %37, %38, %39, %40, %41, %42, %43, %44, %45, %46, %47, %48, %49, %50, %51, %52, %53, %54, %55, %56, %57, %58, %59, %60, %61, %62, %63, %64, %65, %66, %67, %68, %69, %70, %71, %72, %73, %74, %75, %76, %77, %78, %79}, %80, %81, p, 1, 1, 1, 0;\n}\n"
        : "+f"(d[0]), "+f"(d[1]), "+f"(d[2]), "+f"(d[3]), "+f"(d[4]), "+f"(d[5]), "+f"(d[6]), "+f"(d[7]), "+f"(d[8]), "+f"(d[9]), "+f"(d[10]), "+f"(d[11]), "+f"(d[12]), "+f"(d[13]), "+f"(d[14]), "+f"(d[15]), "+f"(d[16]), "+f"(d[17]), "+f"(d[18]), "+f"(d[19]), "+f"(d[20]), "+f"(d[21]), "+f"(d[22]), "+f"(d[23]), "+f"(d[24]), "+f"(d[25]), "+f"(d[26]), "+f"(d[27]), "+f"(d[28]), "+f"(d[29]), "+f"(d[30]), "+f"(d[31]), "+f"(d[32]), "+f"(d[33]), "+f"(d[34]), "+f"(d[35]), "+f"(d[36]), "+f"(d[37]), "+f"(d[38]), "+f"(d[39]), "+f"(d[40]), "+f"(d[41]), "+f"(d[42]), "+f"(d[43]), "+f"(d[44]), "+f"(d[45]), "+f"(d[46]), "+f"(d[47]), "+f"(d[48]), "+f"(d[49]), "+f"(d[50]), "+f"(d[51]), "+f"(d[52]), "+f"(d[53]), "+f"(d[54]), "+f"(d[55]), "+f"(d[56]), "+f"(d[57]), "+f"(d[58]), "+f"(d[59]), "+f"(d[60]), "+f"(d[61]), "+f"(d[62]), "+f"(d[63]), "+f"(d[64]), "+f"(d[65]), "+f"(d[66]), "+f"(d[67]), "+f"(d[68]), "+f"(d[69]), "+f"(d[70]), "+f"(d[71]), "+f"(d[72]), "+f"(d[73]), "+f"(d[74]), "+f"(d[75]), "+f"(d[76]), "+f"(d[77]), "+f"(d[78]), "+f"(d[79])
        : "l"(da), "l"(db), "r"(scale_d));
}

__device__ __forceinline__ void red_release(unsigned int* p) {
    asm volatile("red.release.gpu.global.add.u32 [%0], 1;" ::"l"(p) : "memory");
}
__device__ __forceinline__ unsigned int ld_relaxed(const unsigned int* p) {
    unsigned int v;
    asm volatile("ld.relaxed.gpu.global.u32 %0, [%1];" : "=r"(v) : "l"(p) : "memory");
    return v;
}
__device__ __forceinline__ void spin_until(const unsigned int* p, unsigned int target) {
    int it = 0;
    while (ld_relaxed(p) < target) { if (++it > 20000000) __trap(); }
    unsigned int v;
    asm volatile("ld.acquire.gpu.global.u32 %0, [%1];" : "=r"(v) : "l"(p) : "memory");
}
__device__ __forceinline__ void grid_arrive(int k) {
    __syncthreads();
    if (threadIdx.x == 0) red_release(&g_bar[k]);
}
__device__ __forceinline__ void grid_wait(int k, unsigned int target) {
    if (threadIdx.x == 0) spin_until(&g_bar[k], target);
    __syncthreads();
}

constexpr int SM_STAGE_BYTES = 172032;
constexpr int SM_WF = 90112;
constexpr int SM_WMOD = 131072;
constexpr int G_STAGES = 6, G_STAGE_BYTES = 8192 + 20480;
constexpr int SM_T1 = SM_STAGE_BYTES;
constexpr int SM_T3 = SM_T1 + 5120;
constexpr int SM_T2 = SM_T3 + 5120;
constexpr int SM_TA = SM_T2 + 1024;
constexpr int SM_RED = SM_TA + 1152;
constexpr int SM_SILU = SM_RED + 1280;
constexpr int SM_BARS = SM_SILU + 2560;
constexpr int SM_MODV = SM_BARS + 512;
constexpr int SM_X = SM_MODV + 3840;
constexpr int SM_TOTAL = SM_X + 20480;

struct Params {
    const __nv_bfloat16* x;
    const __nv_bfloat16* w_r;
    const __nv_bfloat16* w_i;
    const __nv_bfloat16* w1;
    const __nv_bfloat16* b1;
    const __nv_bfloat16* w2;
    const __nv_bfloat16* b2;
    const __nv_bfloat16* c;
    const __nv_bfloat16* w_mod;
    __nv_bfloat16* out;
    int stop_after;
};

__device__ __forceinline__ uint32_t badd(uint32_t a, uint32_t b) { uint32_t r; asm("add.rn.bf16x2 %0, %1, %2;" : "=r"(r) : "r"(a), "r"(b)); return r; }
__device__ __forceinline__ uint32_t bsub(uint32_t a, uint32_t b) { uint32_t r; asm("sub.rn.bf16x2 %0, %1, %2;" : "=r"(r) : "r"(a), "r"(b)); return r; }
__device__ __forceinline__ uint32_t bmul(uint32_t a, uint32_t b) { uint32_t r; asm("mul.rn.bf16x2 %0, %1, %2;" : "=r"(r) : "r"(a), "r"(b)); return r; }
__device__ __forceinline__ uint4 ldg128(const void* p) { return __ldg(reinterpret_cast<const uint4*>(p)); }
__device__ __forceinline__ uint4 ldcg128(const void* p) {
    uint4 v;
    asm volatile("ld.global.cg.v4.u32 {%0,%1,%2,%3}, [%4];" : "=r"(v.x), "=r"(v.y), "=r"(v.z), "=r"(v.w) : "l"(p));
    return v;
}
__device__ __forceinline__ void stg128(void* p, uint32_t a, uint32_t b, uint32_t c, uint32_t d) {
    asm volatile("st.global.v4.u32 [%0], {%1,%2,%3,%4};" ::"l"(p), "r"(a), "r"(b), "r"(c), "r"(d) : "memory");
}
__device__ __forceinline__ float2 ldcg64(const float2* p) {
    float2 v;
    asm volatile("ld.global.cg.v2.f32 {%0,%1}, [%2];" : "=f"(v.x), "=f"(v.y) : "l"(p));
    return v;
}

__device__ __forceinline__ void ln_row(uint32_t (&w)[20]) {
    float sa[4] = {0.f, 0.f, 0.f, 0.f};
#pragma unroll
    for (int i = 0; i < 20; i += 2) { sa[0] += bf_lo(w[i]); sa[1] += bf_hi(w[i]); sa[2] += bf_lo(w[i + 1]); sa[3] += bf_hi(w[i + 1]); }
    float s = (sa[0] + sa[1]) + (sa[2] + sa[3]);
#pragma unroll
    for (int m = 8; m >= 1; m >>= 1) s += __shfl_xor_sync(0xffffffffu, s, m);
    const float mu = s * (1.0f / 640.0f);
    float qa[4] = {0.f, 0.f, 0.f, 0.f};
#pragma unroll
    for (int i = 0; i < 20; i += 2) {
        const float d0 = bf_lo(w[i]) - mu, d1 = bf_hi(w[i]) - mu, d2 = bf_lo(w[i + 1]) - mu, d3 = bf_hi(w[i + 1]) - mu;
        qa[0] = fmaf(d0, d0, qa[0]); qa[1] = fmaf(d1, d1, qa[1]); qa[2] = fmaf(d2, d2, qa[2]); qa[3] = fmaf(d3, d3, qa[3]);
    }
    float q = (qa[0] + qa[1]) + (qa[2] + qa[3]);
#pragma unroll
    for (int m = 8; m >= 1; m >>= 1) q += __shfl_xor_sync(0xffffffffu, q, m);
    const float var = bf16r(q * (1.0f / 640.0f));
    const float den = bf16r(sqrtf(bf16r(var + 1e-5f)));
    const float r = __fdiv_rn(1.0f, den);
    const uint32_t m2 = pack_bf16(mu, mu);
#pragma unroll
    for (int i = 0; i < 20; i++) {
        const uint32_t d = bsub(w[i], m2);
        w[i] = pack_bf16(bf_lo(d) * r, bf_hi(d) * r);
    }
}
__device__ __forceinline__ void unpack4(uint32_t* w, uint4 v) { w[0] = v.x; w[1] = v.y; w[2] = v.z; w[3] = v.w; }

__device__ __forceinline__ void gemm_consumer(float (&acc)[80], uint32_t sm_base_u, uint32_t fullb, int NK, int tid) {
    const uint32_t emptyb = fullb + 64;
    const uint64_t da0 = make_desc(sm_base_u, 8192, 1024);
    const uint64_t db0 = make_desc(sm_base_u + 8192, 16, 1024);
    uint32_t ph = 0;
    mbar_wait(fullb, 0);
#pragma unroll 1
    for (int kb0 = 0; kb0 < NK; kb0 += G_STAGES) {
#pragma unroll
        for (int s = 0; s < G_STAGES; s++) {
            const int kb = kb0 + s;
            if (kb < NK) {
                constexpr uint64_t one = 1;
                const uint64_t so = one * ((s * G_STAGE_BYTES) >> 4);
                WG_FENCE();
#pragma unroll
                for (int k = 0; k < 4; k++) wgmma_tn_160(acc, da0 + so + k * 128, db0 + so + k * 2, (kb > 0 || k > 0) ? 1 : 0);
                WG_COMMIT();
                const int sn = (s + 1) % G_STAGES;
                if (kb + 1 < NK) mbar_wait(fullb + 8 * sn, (s + 1 == G_STAGES) ? ph ^ 1 : ph);
                wg_wait<1>();
                if (kb > 0 && tid == 0) mbar_arrive(emptyb + 8 * ((s + G_STAGES - 1) % G_STAGES));
            }
        }
        ph ^= 1;
    }
}

__device__ __forceinline__ void load_wmod_slab(const CUtensorMap* tm, uint32_t dst, int cta, uint32_t bar) {
    mbar_expect(bar, 640 * 64);
#pragma unroll
    for (int i = 0; i < 5; i++) tma2d(dst + i * 128 * 64, tm, cta * 32, i * 128, bar);
}
__device__ __forceinline__ void mod_partial(const unsigned char* slab, const float* s_silu, float* s_red, int tid) {
    uint4 wm[8];
#pragma unroll
    for (int i = 0; i < 8; i++) wm[i] = *reinterpret_cast<const uint4*>(slab + ((tid >> 2) + 80 * i) * 64 + (tid & 3) * 16);
    float acc[8];
#pragma unroll
    for (int e = 0; e < 8; e++) acc[e] = 0.f;
#pragma unroll
    for (int i = 0; i < 8; i++) {
        const float sv = s_silu[(tid >> 2) + 80 * i];
        acc[0] = fmaf(sv, bf_lo(wm[i].x), acc[0]); acc[1] = fmaf(sv, bf_hi(wm[i].x), acc[1]);
        acc[2] = fmaf(sv, bf_lo(wm[i].y), acc[2]); acc[3] = fmaf(sv, bf_hi(wm[i].y), acc[3]);
        acc[4] = fmaf(sv, bf_lo(wm[i].z), acc[4]); acc[5] = fmaf(sv, bf_hi(wm[i].z), acc[5]);
        acc[6] = fmaf(sv, bf_lo(wm[i].w), acc[6]); acc[7] = fmaf(sv, bf_hi(wm[i].w), acc[7]);
    }
    const int lane = tid & 31;
    const bool u16 = lane & 16, u8 = lane & 8, u4 = lane & 4;
    float b4[4], b2[2], b1;
#pragma unroll
    for (int e = 0; e < 4; e++) {
        const float keep = u16 ? acc[e + 4] : acc[e], send = u16 ? acc[e] : acc[e + 4];
        b4[e] = keep + __shfl_xor_sync(0xffffffffu, send, 16);
    }
#pragma unroll
    for (int e = 0; e < 2; e++) {
        const float keep = u8 ? b4[e + 2] : b4[e], send = u8 ? b4[e] : b4[e + 2];
        b2[e] = keep + __shfl_xor_sync(0xffffffffu, send, 8);
    }
    {
        const float keep = u4 ? b2[1] : b2[0], send = u4 ? b2[0] : b2[1];
        b1 = keep + __shfl_xor_sync(0xffffffffu, send, 4);
    }
    s_red[(tid >> 5) * 32 + (lane & 3) * 8 + (u16 ? 4 : 0) + (u8 ? 2 : 0) + (u4 ? 1 : 0)] = b1;
}

__device__ __forceinline__ void prefetch_chunk(const void* base, int cta, int half, int tid) {
    if (tid == 288 && cta < 128)
        asm volatile("cp.async.bulk.prefetch.L2.global [%0], %1;" ::"l"((const char*)base + (cta * 2 + half) * 27648), "r"(27648));
}

__global__ void __launch_bounds__(NT, 1)
fused_kernel(const __grid_constant__ CUtensorMap tm_h2, const __grid_constant__ CUtensorMap tm_w1,
             const __grid_constant__ CUtensorMap tm_w2, const __grid_constant__ CUtensorMap tm_u,
             const __grid_constant__ CUtensorMap tm_wm, const __grid_constant__ CUtensorMap tm_x, const Params p) {
    extern __shared__ unsigned char sm_raw[];
    const uint32_t sm_base_u = __shfl_sync(0xffffffffu, (smem_u32(sm_raw) + 1023u) & ~1023u, 0);
    unsigned char* sm = sm_raw + (sm_base_u - smem_u32(sm_raw));
    float2* s_t1 = reinterpret_cast<float2*>(sm + SM_T1);
    float2* s_t3 = reinterpret_cast<float2*>(sm + SM_T3);
    float2* s_t2 = reinterpret_cast<float2*>(sm + SM_T2);
    float2* s_ta = reinterpret_cast<float2*>(sm + SM_TA);
    float* s_red = reinterpret_cast<float*>(sm + SM_RED);
    const uint32_t bars = sm_base_u + SM_BARS;

    const int tid = threadIdx.x, lane = tid & 31;
    const int warp = __shfl_sync(0xffffffffu, tid >> 5, 0);
    const int cta = blockIdx.x;
    const int s0 = cta;
    const int lrow = 2 * warp + (lane >> 4);
    const int ll = lane & 15;
    TSTAMP(0);

    float* s_silu = reinterpret_cast<float*>(sm + SM_SILU);
    const uint32_t bar_x = bars + 256, bar_w = bars + 264;
    if (tid == 288) {
        for (int i = 0; i < 8; i++) { mbar_init(bars + 8 * i, 1); mbar_init(bars + 64 + 8 * i, 1); mbar_init(bars + 128 + 8 * i, 1); mbar_init(bars + 192 + 8 * i, 1); }
        mbar_init(bar_x, 1); mbar_init(bar_w, 1);
        asm volatile("fence.mbarrier_init.release.cluster;" ::: "memory");
        if (cta < 40) load_wmod_slab(&tm_wm, sm_base_u + SM_WMOD, cta, bar_w);
        if (cta == 0) g_bar[4] = 0;
        __nanosleep(400);
        if (cta < 128) {
            mbar_expect(bar_x, 16 * 1280);
#pragma unroll
            for (int i = 0; i < 5; i++) tma3d(sm_base_u + SM_X + i * 4096, &tm_x, i * 128, 0, s0, bar_x);
        }
    }
    uint4 cvv = make_uint4(0, 0, 0, 0);
    if (tid >= 208 && tid < 288) cvv = ldg128(p.c + (tid - 208) * 8);
    uint32_t xw[20];
    TSTAMP(17);
#pragma unroll 1
    for (int i = tid; i < 1552 && tid < 288; i += 288) {
        float ang;
        if (i < 640) ang = (float)((i % 80) * (i / 80)) * (1.0f / 320.0f);
        else if (i < 1280) ang = (float)(((i - 640) & 31) * ((i - 640) >> 5)) * (1.0f / 320.0f);
        else if (i < 1408) ang = (float)(((i - 1280) & 15) * ((i - 1280) >> 4)) * (1.0f / 64.0f);
        else ang = (float)(((128 * ((i - 1408) & 15) + s0) * ((i - 1408) >> 4)) & 2047) * (1.0f / 1024.0f);
        float s, c;
        sincospif(-ang, &s, &c);
        s_t1[i] = make_float2(c, s);
    }
    if (tid >= 208 && tid < 288) {
        const uint32_t w4[4] = {cvv.x, cvv.y, cvv.z, cvv.w};
        float o[8];
#pragma unroll
        for (int e = 0; e < 4; e++) {
            const float c0 = bf_lo(w4[e]), c1 = bf_hi(w4[e]);
            o[2 * e] = bf16r(__fdividef(c0, 1.0f + exp2f(-1.4426950409f * c0)));
            o[2 * e + 1] = bf16r(__fdividef(c1, 1.0f + exp2f(-1.4426950409f * c1)));
        }
        *reinterpret_cast<float4*>(s_silu + (tid - 208) * 8) = make_float4(o[0], o[1], o[2], o[3]);
        *reinterpret_cast<float4*>(s_silu + (tid - 208) * 8 + 4) = make_float4(o[4], o[5], o[6], o[7]);
    }
    TSTAMP(18);
    __syncthreads();
    if (cta < 40) { mbar_wait(bar_w, 0); mod_partial(sm + SM_WMOD, s_silu, s_red, tid); }
    TSTAMP(19);
    __syncthreads();
    TSTAMP(20);
    if (cta < 40 && warp == 9) {
        float t = 0.f;
#pragma unroll
        for (int w = 0; w < 10; w++) t += s_red[w * 32 + lane];
        TSTAMPT(22, 288);
        asm volatile("st.relaxed.gpu.global.u32 [%0], %1;" ::"l"(&g_modw[cta * 32 + lane]), "r"(0x80000000u | (pack_bf16(t, 0.f) & 0xffffu)) : "memory");
        TSTAMPT(23, 288);
    }
    if (tid == 288) {
        const uint32_t cW = 9968;
        const uint32_t off = cta * cW, n = min(cW, 1314816u - min(off, 1314816u));
        if (n) {
            asm volatile("cp.async.bulk.prefetch.L2.global [%0], %1;" ::"l"((const char*)p.w_r + off), "r"(n));
            asm volatile("cp.async.bulk.prefetch.L2.global [%0], %1;" ::"l"((const char*)p.w_i + off), "r"(n));
        }
        if (cta >= 40 && cta < 120) load_wmod_slab(&tm_wm, sm_base_u + SM_WMOD, cta, bar_w);
        asm volatile("prefetch.tensormap [%0];" ::"l"(&tm_h2) : "memory");
        asm volatile("prefetch.tensormap [%0];" ::"l"(&tm_w1) : "memory");
        asm volatile("prefetch.tensormap [%0];" ::"l"(&tm_w2) : "memory");
        asm volatile("prefetch.tensormap [%0];" ::"l"(&tm_u) : "memory");
    }

    if (cta == 128 && tid < 256) {
        const int q = 8 * (tid >> 7), ks = q + 16 * (tid & 127), ksm = (2048 - ks) & 2047;
        reinterpret_cast<float2*>(sm + SM_WF)[tid] =
            make_float2(0.5f * (__bfloat162float(__ldg(p.w_r + ks * DF_ + 320)) + __bfloat162float(__ldg(p.w_r + ksm * DF_ + 320))),
                        0.5f * (__bfloat162float(__ldg(p.w_i + ks * DF_ + 320)) - __bfloat162float(__ldg(p.w_i + ksm * DF_ + 320))));
    }

    if (cta < 128) {
        uint32_t afr[3][4];
        {
            const int g = lane >> 2, t = lane & 3;
            const float scale = 1.0f / (2048.0f * 640.0f);
            float cr[4], ci[4];
#pragma unroll
            for (int i = 0; i < 4; i++) {
                const int j = 2 * t + (i & 1) + (i >> 1) * 8;
                const float2 w = s_ta[g * 16 + j];
                cr[i] = w.x * scale;
                ci[i] = (g == 0 ? ((i & 1) ? -1.0f : 1.0f) : w.y) * scale;
            }
#pragma unroll
            for (int l = 0; l < 3; l++) {
                afr[l][0] = pack_bf16(cr[0], cr[1]);
                afr[l][1] = pack_bf16(ci[0], ci[1]);
                afr[l][2] = pack_bf16(cr[2], cr[3]);
                afr[l][3] = pack_bf16(ci[2], ci[3]);
                cr[0] -= bf_lo(afr[l][0]); cr[1] -= bf_hi(afr[l][0]); ci[0] -= bf_lo(afr[l][1]); ci[1] -= bf_hi(afr[l][1]);
                cr[2] -= bf_lo(afr[l][2]); cr[3] -= bf_hi(afr[l][2]); ci[2] -= bf_lo(afr[l][3]); ci[3] -= bf_hi(afr[l][3]);
            }
        }
        if (warp < 8) {
            mbar_wait(bar_x, 0);
#pragma unroll
            for (int i = 0; i < 5; i++) unpack4(xw + 4 * i, *reinterpret_cast<const uint4*>(sm + SM_X + i * 4096 + lrow * 256 + ll * 16));
            ln_row(xw);
            TSTAMP(1);
        } else {
#pragma unroll 1
            for (int c = tid - 256; c < 160; c += 64) {
                uint4 a, b;
                int it = 0;
                do {
                    asm volatile("ld.relaxed.gpu.global.v4.u32 {%0,%1,%2,%3}, [%4];" : "=r"(a.x), "=r"(a.y), "=r"(a.z), "=r"(a.w) : "l"(g_modw + c * 8) : "memory");
                    asm volatile("ld.relaxed.gpu.global.v4.u32 {%0,%1,%2,%3}, [%4];" : "=r"(b.x), "=r"(b.y), "=r"(b.z), "=r"(b.w) : "l"(g_modw + c * 8 + 4) : "memory");
                    if (++it > 20000000) __trap();
                } while (((a.x & a.y & a.z & a.w & b.x & b.y & b.z & b.w) >> 31) == 0);
                *reinterpret_cast<uint4*>(sm + SM_MODV + c * 16) =
                    make_uint4(__byte_perm(a.x, a.y, 0x5410), __byte_perm(a.z, a.w, 0x5410), __byte_perm(b.x, b.y, 0x5410), __byte_perm(b.z, b.w, 0x5410));
            }
            prefetch_chunk(p.w1, cta, 0, tid);
            const int r = cta >> 4, b = cta & 15;
            const int q = r ? r : ((b < 8) ? 0 : 8);
            const bool cj = r && b >= 8;
            const int colw = cj ? 601 - 40 * b : 40 * (b & 7);
            const int t6 = tid - 256, pp0 = t6 / 6, ch = t6 - pp0 * 6;
            if (t6 < 60) {
#pragma unroll 1
                for (int pp = pp0; pp < 128; pp += 10) {
                    const int ks = q + 16 * pp;
                    const int al = ((((cj ? 2048 - ks : ks) * DF_ + colw) * 2) & ~15) + 16 * ch;
                    if (al + 16 <= S_ * DF_ * 2) {
                        asm volatile("cp.async.cg.shared.global [%0], [%1], 16;" ::"r"(sm_base_u + SM_WF + pp * 96 + ch * 16), "l"((const char*)p.w_r + al) : "memory");
                        asm volatile("cp.async.cg.shared.global [%0], [%1], 16;" ::"r"(sm_base_u + SM_WF + 12288 + pp * 96 + ch * 16), "l"((const char*)p.w_i + al) : "memory");
                    }
                }
            }
            asm volatile("cp.async.commit_group;" ::: "memory");
        }
        __syncthreads();
        TSTAMP(2);
        CLK(0);
        if (warp < 8) {
            uint4 sa[5], ca[5];
#pragma unroll
            for (int i = 0; i < 5; i++) {
                sa[i] = *reinterpret_cast<const uint4*>(sm + SM_MODV + (ll + 16 * i) * 16);
                ca[i] = *reinterpret_cast<const uint4*>(sm + SM_MODV + 1280 + (ll + 16 * i) * 16);
            }
            const uint32_t one2 = 0x3f803f80u;
#pragma unroll
            for (int i = 0; i < 5; i++) {
                uint4 h;
                h.x = badd(bmul(xw[4 * i + 0], badd(one2, ca[i].x)), sa[i].x);
                h.y = badd(bmul(xw[4 * i + 1], badd(one2, ca[i].y)), sa[i].y);
                h.z = badd(bmul(xw[4 * i + 2], badd(one2, ca[i].z)), sa[i].z);
                h.w = badd(bmul(xw[4 * i + 3], badd(one2, ca[i].w)), sa[i].w);
                *reinterpret_cast<uint4*>(sm + lrow * 1296 + (ll + 16 * i) * 16) = h;
            }
        }
        CLK(1);
        __syncthreads();
        CLK(2);
        float2* s_f = reinterpret_cast<float2*>(sm + 24576);
        constexpr int PB2 = 24, PK = 121, PR = 968;
        {
            const int g = lane >> 2, t = lane & 3;
            float2 z0[8], z1[8];
            const uint32_t laddr = sm_base_u + (((lane >> 3) & 1) * 8 + (lane & 7)) * 1296 + (80 * (lane >> 4) + 8 * warp) * 2;
#pragma unroll
            for (int ap = 0; ap < 4; ap++) {
                uint32_t b0, b1, b2, b3;
                asm volatile("ldmatrix.sync.aligned.m8n8.x4.trans.shared.b16 {%0,%1,%2,%3}, [%4];"
                             : "=r"(b0), "=r"(b1), "=r"(b2), "=r"(b3) : "r"(laddr + ap * 320));
#pragma unroll
                for (int h = 0; h < 2; h++) {
                    float c0 = 0.f, c1 = 0.f, c2 = 0.f, c3 = 0.f;
                    const uint32_t bb0 = h ? b2 : b0, bb1 = h ? b3 : b1;
#pragma unroll
                    for (int l = 2; l >= 0; l--) {
                        asm volatile("mma.sync.aligned.m16n8k16.row.col.f32.bf16.bf16.f32 {%0,%1,%2,%3}, {%4,%5,%6,%7}, {%8,%9}, {%0,%1,%2,%3};"
                                     : "+f"(c0), "+f"(c1), "+f"(c2), "+f"(c3)
                                     : "r"(afr[l][0]), "r"(afr[l][1]), "r"(afr[l][2]), "r"(afr[l][3]), "r"(bb0), "r"(bb1));
                    }
                    z0[2 * ap + h] = make_float2(c0, c2);
                    z1[2 * ap + h] = make_float2(c1, c3);
                }
            }
            fft8<-1>(z0);
            fft8<-1>(z1);
            const int b = 8 * warp + 2 * t;
            float2* d0 = s_f + g * PR + (b % 5) * PB2 + ((13 * b) & 15);
            float2* d1 = s_f + g * PR + ((b + 1) % 5) * PB2 + ((13 * (b + 1)) & 15);
            d0[0] = z0[0]; d1[0] = z1[0];
#pragma unroll
            for (int k1 = 1; k1 < 8; k1++) {
                const float4 tw = *reinterpret_cast<const float4*>(&s_t1[k1 * 80 + b]);
                d0[k1 * PK] = cmul(z0[k1], make_float2(tw.x, tw.y));
                d1[k1 * PK] = cmul(z1[k1], make_float2(tw.z, tw.w));
            }
        }
        CLK(3);
        __syncthreads();
        CLK(4);
#pragma unroll 1
        for (int i = tid; i < 1024; i += NT) {
            float2* base = s_f + (i >> 7) * PR + ((i >> 4) & 7) * PK + (i & 15);
            float2 v0 = base[0], v1 = base[PB2], v2 = base[2 * PB2], v3 = base[3 * PB2], v4 = base[4 * PB2];
            fft5<-1>(v0, v1, v2, v3, v4);
            base[0] = v0; base[PB2] = v1; base[2 * PB2] = v2; base[3 * PB2] = v3; base[4 * PB2] = v4;
        }
        CLK(5);
        __syncthreads();
        CLK(6);
        {
            const int r = tid / 40, u = tid - r * 40;
            const float2* base = s_f + r * PR + (u & 7) * PK + (u >> 3) * PB2;
            float2 v[16];
#pragma unroll
            for (int b1 = 0; b1 < 16; b1++) v[b1] = base[b1];
            fft16<-1>(v);
            if (r > 0) {
                float2* dst = g_buf + ((size_t)r * 128 + s0) * 640 + u;
#pragma unroll
                for (int c1 = 0; c1 < 16; c1++) dst[c1 * 40] = v[c1];
            } else {
                float2* s_z = reinterpret_cast<float2*>(sm);
                const int m0 = 16 * (u >> 3);
#pragma unroll
                for (int c1 = 0; c1 < 16; c1++) {
                    int m = (65 * c1) % 80 + m0;
                    if (m >= 80) m -= 80;
                    s_z[(u & 7) + 8 * m] = v[c1];
                }
            }
        }
        CLK(7);
        __syncthreads();
        CLK(8);
        {
            const float2* s_z = reinterpret_cast<const float2*>(sm);
            const float2 tw8 = s_ta[8 * 16];
            float2* dst = g_buf + (size_t)s0 * 640;
#pragma unroll 1
            for (int k = tid; k <= 320; k += NT) {
                const float2 a = s_z[k], b = s_z[(640 - k) % 640];
                const float2 T0 = make_float2(0.5f * (a.x + b.x), 0.5f * (a.y - b.y));
                float2 T8 = make_float2(0.5f * (a.y + b.y), -0.5f * (a.x - b.x));
                T8 = cmul(T8, tw8);
                if (k < 320) { dst[k] = T0; dst[320 + k] = T8; }
                else { g_ext[s0] = T0; g_ext[128 + s0] = T8; }
            }
        }
    }
    CLK(9);
    TSTAMP(3);
    grid_arrive(1);
    DBG_STOP(1);

    {
        const int t = lane >> 2;
        const int il = lane & 3;
        float2* colp = g_buf;
        int stride = 640;
        const bool act = cta < 128 || (cta == 128 && warp == 0);
        bool do_store = true;
        float2 wf[16];
        const int r = cta >> 4, b = cta & 15;
        const int q = r ? r : ((b < 8) ? 0 : 8);
        const bool cj = r && b >= 8;
        const int col0 = cj ? 601 - 40 * b : 40 * (b & 7) + (r ? 0 : 0);
        if (cta < 128) {
            const int u = warp * 4 + il;
            if (r) {
                const int kd = 40 * b + u, m = kd >> 3;
                colp = g_buf + (size_t)r * 128 * 640 + (m & 15) * 40 + (m % 5) * 8 + (kd & 7);
            } else {
                colp = g_buf + 40 * b + u;
            }
        } else if (act) { colp = g_ext + (il & 1) * 128; stride = 1; do_store = il < 2; }
        if (cta >= 40 && cta < 120) {
            mbar_wait(bar_w, 0);
            mod_partial(sm + SM_WMOD, s_silu, s_red, tid);
            __syncthreads();
            if (warp == 9) {
                float tt = 0.f;
#pragma unroll
                for (int w = 0; w < 10; w++) tt += s_red[w * 32 + lane];
                g_mod[cta * 32 + lane] = __float2bfloat16_rn(tt);
            }
        }
        if (cta < 128) {
            asm volatile("cp.async.wait_group 0;" ::: "memory");
            __syncthreads();
            const int colw = r ? col0 : 40 * (b & 7);
            const int u = warp * 4 + il;
            const uint32_t mis = (uint32_t)(((cj ? 2048 - q : q) * DF_ + colw) * 2) & 15u;
            const unsigned char* wp = sm + SM_WF + 2 * t * 96 + mis + 2 * (cj ? 39 - u : u);
            const float sg = cj ? -1.0f : 1.0f;
#pragma unroll
            for (int e = 0; e < 2; e++)
#pragma unroll
                for (int k2 = 0; k2 < 8; k2++) {
                    const int o = (e + 16 * k2) * 96;
                    wf[e * 8 + k2] = make_float2(__bfloat162float(*reinterpret_cast<const __nv_bfloat16*>(wp + o)),
                                                 sg * __bfloat162float(*reinterpret_cast<const __nv_bfloat16*>(wp + 12288 + o)));
                }
            if ((b & 7) == 0 && u == 0) {
                const int kc = cj ? 320 : 0;
                float2 ot[16];
#pragma unroll
                for (int i = 0; i < 16; i++) {
                    const int ks = q + 32 * t + 16 * (i >> 3) + 256 * (i & 7);
                    const int orow = cj ? ks : ((2048 - ks) & 2047);
                    ot[i] = make_float2(__bfloat162float(__ldg(p.w_r + orow * DF_ + kc)), __bfloat162float(__ldg(p.w_i + orow * DF_ + kc)));
                }
#pragma unroll
                for (int i = 0; i < 16; i++) wf[i] = make_float2(0.5f * (wf[i].x + ot[i].x), 0.5f * (wf[i].y - sg * ot[i].y));
            }
        } else if (act) {
            const float2* tab = reinterpret_cast<const float2*>(sm + SM_WF) + (il & 1) * 128 + 2 * t;
#pragma unroll
            for (int i = 0; i < 16; i++) wf[i] = tab[(i >> 3) + 16 * (i & 7)];
        }
        TSTAMP(4);
        grid_wait(1, NCTA);
        TSTAMP(5);
        CLK(10);
        prefetch_chunk(p.w1, cta, 1, tid);
        if (cta < 40 && warp == 9) g_modw[cta * 32 + lane] = 0;
        if (act) {
            float4* s_x = reinterpret_cast<float4*>(sm) + warp * (8 * 36);
            float2 v[16];
            float2* sp = colp + t * stride;
            const int st8 = 8 * stride;
#pragma unroll
            for (int n1 = 0; n1 < 16; n1++) v[n1] = ldcg64(sp + n1 * st8);
            CLK(11);
            fft16<-1>(v);
            CLK(12);
#pragma unroll
            for (int m = 0; m < 8; m++) {
                const float4 tw = *reinterpret_cast<const float4*>(&s_t2[t * 16 + 2 * m]);
                const float2 a = m ? cmul(v[2 * m], make_float2(tw.x, tw.y)) : v[0];
                const float2 b = cmul(v[2 * m + 1], make_float2(tw.z, tw.w));
                s_x[m * 36 + lane] = make_float4(a.x, a.y, b.x, b.y);
            }
            __syncwarp();
            float2 a[8], b[8];
#pragma unroll
            for (int n2 = 0; n2 < 8; n2++) {
                const float4 u = s_x[t * 36 + n2 * 4 + il];
                a[n2] = make_float2(u.x, u.y); b[n2] = make_float2(u.z, u.w);
            }
            fft8<-1>(a);
            fft8<-1>(b);
#pragma unroll
            for (int k2 = 0; k2 < 8; k2++) { a[k2] = cmul(a[k2], wf[k2]); b[k2] = cmul(b[k2], wf[8 + k2]); }
            fft8<1>(a);
            fft8<1>(b);
            __syncwarp();
#pragma unroll
            for (int n2 = 0; n2 < 8; n2++) {
                const float4 tw = *reinterpret_cast<const float4*>(&s_t2[n2 * 16 + 2 * t]);
                const float2 ua = n2 ? cmulc(a[n2], make_float2(tw.x, tw.y)) : a[0];
                const float2 ub = n2 ? cmulc(b[n2], make_float2(tw.z, tw.w)) : b[0];
                s_x[t * 36 + n2 * 4 + il] = make_float4(ua.x, ua.y, ub.x, ub.y);
            }
            __syncwarp();
#pragma unroll
            for (int m = 0; m < 8; m++) {
                const float4 u = s_x[m * 36 + lane];
                v[2 * m] = make_float2(u.x, u.y); v[2 * m + 1] = make_float2(u.z, u.w);
            }
            CLK(13);
            fft16<1>(v);
            CLK(14);
            if (do_store) {
#pragma unroll
                for (int n1 = 0; n1 < 16; n1++) sp[n1 * st8] = v[n1];
            }
        }
    }
    CLK(15);
    TSTAMP(6);
    grid_arrive(2);
    DBG_STOP(2);

    {
        grid_wait(2, NCTA);
        TSTAMP(7);
        CLK(16);
        prefetch_chunk(p.w2, cta, 0, tid);
        if (cta == 0 && tid == 0) g_bar[1] = 0;
        if (cta < 128) {
            float2* s_a = reinterpret_cast<float2*>(sm);
            constexpr int A_D1 = 33, A_ROW = 20 * 33 + 2;
            float2* s_b = reinterpret_cast<float2*>(sm + 49152);
            constexpr int B_BETA = 16 * 20 + 4, B_ROW = 2 * B_BETA + 8;
            unsigned char* s_y = sm + 98304;
            float2* s_z = reinterpret_cast<float2*>(sm + 126976);
            if (warp >= 8) {
                const float2 tw8 = s_ta[8 * 16];
                const float2* src = g_buf + (size_t)s0 * 640;
                float2 U0[6], U8[6];
                uint4 mv[4];
#pragma unroll
                for (int i = 0; i < 6; i++) {
                    const int k = tid - 256 + 64 * i;
                    const bool in = k < 320;
                    U0[i] = ldcg64(in ? src + k : g_ext + s0);
                    U8[i] = ldcg64(in ? src + 320 + k : g_ext + 128 + s0);
                }
#pragma unroll
                for (int i = 0; i < 4; i++) if (tid - 256 + 64 * i < 240) mv[i] = ldcg128(g_mod + 2 * 640 + (tid - 256 + 64 * i) * 8);
#pragma unroll
                for (int i = 0; i < 6; i++) {
                    const int k = tid - 256 + 64 * i;
                    const float2 a = U0[i], b = cmulc(U8[i], tw8);
                    if (k <= 320) s_z[k] = make_float2(a.x - b.y, a.y + b.x);
                    if (k > 0 && k < 320) s_z[640 - k] = make_float2(a.x + b.y, b.x - a.y);
                }
                asm volatile("bar.sync 2, 96;" ::: "memory");
#pragma unroll
                for (int i = 0; i < 4; i++) if (tid - 256 + 64 * i < 240) *reinterpret_cast<uint4*>(sm + SM_MODV + (tid - 256 + 64 * i) * 16) = mv[i];
            }
            if (warp < 8) {
                const int r = warp, kb = lane;
                float2 v[20];
                if (r > 0) {
                    const float2* src = g_buf + ((size_t)r * 128 + s0) * 640;
                    const int h = kb >> 3;
                    const float2* bj[5];
#pragma unroll
                    for (int j = 0; j < 5; j++) bj[j] = src + h * 40 + ((j + h) % 5) * 8 + (kb & 7);
#pragma unroll
                    for (int ka = 0; ka < 20; ka++) v[ka] = ldcg64(bj[(4 * ka) % 5] + ((4 * ka) & 15) * 40);
                } else {
                    asm volatile("bar.sync 2, 96;" ::: "memory");
#pragma unroll
                    for (int ka = 0; ka < 20; ka++) v[ka] = s_z[32 * ka + kb];
                }
                CLK(17);
                fft20<1>(v);
                CLK(18);
                float2* d = s_a + r * A_ROW + kb;
                d[0] = v[0];
#pragma unroll
                for (int d1 = 1; d1 < 20; d1++) d[d1 * A_D1] = cmulc(v[d1], s_t3[d1 * 32 + kb]);
            }
            CLK(19);
            __syncthreads();
            CLK(20);
            {
                const int r = tid / 40, u = tid - r * 40, beta = u >= 20, d1 = u - 20 * beta;
                const float2* sp = s_a + r * A_ROW + d1 * A_D1 + beta;
                float2 v[16];
#pragma unroll
                for (int al = 0; al < 16; al++) v[al] = sp[2 * al];
                fft16<1>(v);
                float2* dp = s_b + r * B_ROW + beta * B_BETA + d1;
#pragma unroll
                for (int d2 = 0; d2 < 16; d2++) dp[d2 * 20] = v[d2];
            }
            CLK(21);
            __syncthreads();
            CLK(22);
            {
                const float2 w32 = s_t3[10 * 32 + 2 * (tid / 20)];
                float2 Z[16];
#pragma unroll
                for (int r = 0; r < 8; r++) {
                    const float2 v0 = s_b[r * B_ROW + tid];
                    const float2 v1 = cmulc(s_b[r * B_ROW + B_BETA + tid], w32);
                    float2 A = cadd(v0, v1), B = csub(v0, v1);
                    if (r > 0) {
                        const float2 rho = s_ta[r * 16];
                        A = cmulc(A, rho); B = cmulc(B, rho);
                        Z[r] = make_float2(A.x - B.y, A.y + B.x);
                        Z[16 - r] = make_float2(A.x + B.y, B.x - A.y);
                    } else {
                        Z[0] = make_float2(A.x, B.x);
                        Z[8] = make_float2(A.y, B.y);
                    }
                }
                fft16<1>(Z);
                __nv_bfloat16* yp = reinterpret_cast<__nv_bfloat16*>(s_y) + tid;
#pragma unroll
                for (int j = 0; j < 16; j++) {
                    yp[j * 648] = __float2bfloat16_rn(Z[j].x);
                    yp[j * 648 + 320] = __float2bfloat16_rn(Z[j].y);
                }
            }
            CLK(23);
            uint4 ga[5];
            __syncthreads();
            CLK(24);
            if (warp < 8) {
                const size_t rowoff = (size_t)(128 * lrow + s0) * D_;
                const uint32_t one2 = 0x3f803f80u;
#pragma unroll
                for (int i = 0; i < 5; i++) {
                    ga[i] = *reinterpret_cast<const uint4*>(sm + SM_MODV + (ll + 16 * i) * 16);
                }
#pragma unroll
                for (int i = 0; i < 5; i++) {
                    const uint4 y = *reinterpret_cast<const uint4*>(s_y + lrow * 1296 + (ll + 16 * i) * 16);
                    unpack4(xw + 4 * i, *reinterpret_cast<const uint4*>(sm + SM_X + i * 4096 + lrow * 256 + ll * 16));
                    xw[4 * i + 0] = badd(xw[4 * i + 0], bmul(ga[i].x, y.x));
                    xw[4 * i + 1] = badd(xw[4 * i + 1], bmul(ga[i].y, y.y));
                    xw[4 * i + 2] = badd(xw[4 * i + 2], bmul(ga[i].z, y.z));
                    xw[4 * i + 3] = badd(xw[4 * i + 3], bmul(ga[i].w, y.w));
                    stg128(g_x1 + rowoff + (ll + 16 * i) * 8, xw[4 * i], xw[4 * i + 1], xw[4 * i + 2], xw[4 * i + 3]);
                }
                CLK(25);
#pragma unroll 1
                for (int it = 0; it < 2; it++) {
                    ln_row(xw);
                    if (it == 0) {
#pragma unroll
                        for (int i = 0; i < 5; i++) {
                            const uint4 sb = *reinterpret_cast<const uint4*>(sm + SM_MODV + 1280 + (ll + 16 * i) * 16);
                            const uint4 cb = *reinterpret_cast<const uint4*>(sm + SM_MODV + 2560 + (ll + 16 * i) * 16);
                            xw[4 * i + 0] = badd(bmul(xw[4 * i + 0], badd(one2, cb.x)), sb.x);
                            xw[4 * i + 1] = badd(bmul(xw[4 * i + 1], badd(one2, cb.y)), sb.y);
                            xw[4 * i + 2] = badd(bmul(xw[4 * i + 2], badd(one2, cb.z)), sb.z);
                            xw[4 * i + 3] = badd(bmul(xw[4 * i + 3], badd(one2, cb.w)), sb.w);
                        }
                    }
                }
                CLK(26);
#pragma unroll
                for (int i = 0; i < 5; i++)
                    *reinterpret_cast<uint4*>(sm + lrow * 1296 + (ll + 16 * i) * 16) = make_uint4(xw[4 * i], xw[4 * i + 1], xw[4 * i + 2], xw[4 * i + 3]);
            }
            CLK(27);
            __syncthreads();
            CLK(28);
            {
#pragma unroll
                for (int it = 0; it < 2; it++) {
                    const int dp = (tid >> 1) + 160 * it, h = tid & 1;
                    uint32_t w[8];
#pragma unroll
                    for (int j = 0; j < 8; j++) w[j] = *reinterpret_cast<const uint32_t*>(sm + (8 * h + j) * 1296 + dp * 4);
                    stg128(g_h2 + (size_t)(2 * dp) * H2P + 16 * s0 + 8 * h,
                           __byte_perm(w[0], w[1], 0x5410), __byte_perm(w[2], w[3], 0x5410), __byte_perm(w[4], w[5], 0x5410), __byte_perm(w[6], w[7], 0x5410));
                    stg128(g_h2 + (size_t)(2 * dp + 1) * H2P + 16 * s0 + 8 * h,
                           __byte_perm(w[0], w[1], 0x7632), __byte_perm(w[2], w[3], 0x7632), __byte_perm(w[4], w[5], 0x7632), __byte_perm(w[6], w[7], 0x7632));
                }
            }
        }
    }
    CLK(29);
    TSTAMP(8);
    asm volatile("fence.proxy.async.shared::cta;" ::: "memory");
    grid_arrive(3);
    DBG_STOP(3);

#pragma unroll 1
    for (int g = 0; g < 2; g++) {
        if (tid == 128) {
            asm volatile("prefetch.tensormap [%0];" ::"l"(g ? &tm_w2 : &tm_w1) : "memory");
            asm volatile("prefetch.tensormap [%0];" ::"l"(g ? &tm_u : &tm_h2) : "memory");
        }
        grid_wait(3 + g, NCTA);
        TSTAMP(9 + 2 * g);
        CLK(36 + g);
        if (g == 0) prefetch_chunk(p.w2, cta, 1, tid);
        if (cta == 0 && tid == 0) g_bar[2 + g] = 0;
        if (cta < (g ? 128 : 108)) {
            const int mt = cta >> 2, nt = cta & 3;
            const uint32_t fullb = bars + 128 * g, emptyb = fullb + 64;
            const int NK = g ? 27 : 32;
            float* s_c = reinterpret_cast<float*>(sm);
            uint4 bb = make_uint4(0, 0, 0, 0);
            if (g == 0) bb = ldg128(p.b1 + mt * 64 + (tid & 7) * 8);
            else if (warp >= 5) {
                const int t5 = tid - 160;
#pragma unroll
                for (int it = 0; it < 8; it++) {
                    const int i = t5 + it * 160, row = i / 20, c8 = i - row * 20;
                    *reinterpret_cast<uint4*>(sm + SM_X + i * 16) = ldcg128(g_x1 + (size_t)(mt * 64 + row) * D_ + nt * 160 + c8 * 8);
                }
                if (t5 < 20) *reinterpret_cast<uint4*>(sm + SM_MODV + t5 * 16) = ldcg128(g_mod + 5 * 640 + nt * 160 + t5 * 8);
                else if (t5 < 28) *reinterpret_cast<uint4*>(sm + SM_MODV + 320 + (t5 - 20) * 16) = ldg128(p.b2 + mt * 64 + (t5 - 20) * 8);
            }
            if (warp == 4) {
                const CUtensorMap* ta = g ? &tm_w2 : &tm_w1;
                const CUtensorMap* tb = g ? &tm_u : &tm_h2;
                int s = 0; uint32_t ph = 1;
                asm volatile("fence.proxy.async.global;" ::: "memory");
#pragma unroll 1
                for (int kb = 0; kb < NK; kb++) {
                    mbar_wait(emptyb + 8 * s, ph);
                    if (elect_one()) {
                        const uint32_t sa = sm_base_u + s * G_STAGE_BYTES;
                        mbar_expect(fullb + 8 * s, G_STAGE_BYTES);
                        if (g) tma2d(sa, ta, mt * 64, kb * 64, fullb + 8 * s);
                        else tma3d(sa, ta, mt * 64, 0, kb * 4, fullb + 8 * s);
                        tma2d(sa + 8192, tb, kb * 64, nt * 160, fullb + 8 * s);
                    }
                    if (++s == G_STAGES) { s = 0; ph ^= 1; }
                }
            } else if (warp < 4) {
                float acc[80];
                gemm_consumer(acc, sm_base_u, fullb, NK, tid);
                wg_wait<0>();
                CLK(31 + 2 * g);
                TSTAMP(14 + 2 * g);
                asm volatile("bar.sync 1, 128;" ::: "memory");
                CLK(44 + 4 * g);
                if (g == 0) {
                    float* cp = s_c + (2 * (lane & 3)) * 68 + warp * 16 + (lane >> 2);
#pragma unroll
                    for (int i = 0; i < 20; i++) {
                        cp[(i * 8) * 68] = acc[i * 4]; cp[(i * 8 + 1) * 68] = acc[i * 4 + 1];
                        cp[(i * 8) * 68 + 8] = acc[i * 4 + 2]; cp[(i * 8 + 1) * 68 + 8] = acc[i * 4 + 3];
                    }
                } else {
                    float* cp = s_c + (warp * 16 + (lane >> 2)) * 168 + 2 * (lane & 3);
#pragma unroll
                    for (int i = 0; i < 20; i++) {
                        *reinterpret_cast<float2*>(cp + i * 8) = make_float2(acc[i * 4], acc[i * 4 + 1]);
                        *reinterpret_cast<float2*>(cp + 8 * 168 + i * 8) = make_float2(acc[i * 4 + 2], acc[i * 4 + 3]);
                    }
                }
            }
            {
                CLK(45 + 4 * g); __syncthreads(); CLK(46 + 4 * g);
                if (g == 0) {
#pragma unroll 1
                    for (int d = tid >> 3; d < 160; d += NT / 8) {
                        const float4 a0 = *reinterpret_cast<const float4*>(s_c + d * 68 + (tid & 7) * 8);
                        const float4 a1 = *reinterpret_cast<const float4*>(s_c + d * 68 + (tid & 7) * 8 + 4);
                        uint32_t u[4] = {badd(pack_bf16(a0.x, a0.y), bb.x), badd(pack_bf16(a0.z, a0.w), bb.y),
                                         badd(pack_bf16(a1.x, a1.y), bb.z), badd(pack_bf16(a1.z, a1.w), bb.w)};
#pragma unroll
                        for (int e = 0; e < 4; e++) {
                            const float x0 = bf_lo(u[e]), x1 = bf_hi(u[e]);
                            float e0, e1;
                            asm("ex2.approx.ftz.f32 %0, %1;" : "=f"(e0) : "f"(x0 * fmaf(x0 * x0, -0.1029432397f, -2.3022081985f)));
                            asm("ex2.approx.ftz.f32 %0, %1;" : "=f"(e1) : "f"(x1 * fmaf(x1 * x1, -0.1029432397f, -2.3022081985f)));
                            u[e] = pack_bf16(__fdividef(x0, 1.0f + e0), __fdividef(x1, 1.0f + e1));
                        }
                        stg128(g_u + (size_t)(nt * 160 + d) * F_ + mt * 64 + (tid & 7) * 8, u[0], u[1], u[2], u[3]);
                    }
                } else {
#pragma unroll 1
                    for (int i = tid; i < 64 * 20; i += NT) {
                        const int row = i / 20, c8 = i - row * 20;
                        const uint4 xv = *reinterpret_cast<const uint4*>(sm + SM_X + i * 16);
                        const uint4 gb = *reinterpret_cast<const uint4*>(sm + SM_MODV + c8 * 16);
                        const uint32_t b2 = *reinterpret_cast<const unsigned short*>(sm + SM_MODV + 320 + row * 2);
                        const uint32_t b22 = b2 | (b2 << 16);
                        const float4 a0 = *reinterpret_cast<const float4*>(s_c + row * 168 + c8 * 8);
                        const float4 a1 = *reinterpret_cast<const float4*>(s_c + row * 168 + c8 * 8 + 4);
                        const uint32_t o0 = badd(xv.x, bmul(gb.x, badd(pack_bf16(a0.x, a0.y), b22)));
                        const uint32_t o1 = badd(xv.y, bmul(gb.y, badd(pack_bf16(a0.z, a0.w), b22)));
                        const uint32_t o2 = badd(xv.z, bmul(gb.z, badd(pack_bf16(a1.x, a1.y), b22)));
                        const uint32_t o3 = badd(xv.w, bmul(gb.w, badd(pack_bf16(a1.z, a1.w), b22)));
                        stg128(p.out + (size_t)(mt * 64 + row) * D_ + nt * 160 + c8 * 8, o0, o1, o2, o3);
                    }
                }
            }
        }
        CLK(34 + g);
        TSTAMP(10 + 2 * g);
        if (g == 0) {
            asm volatile("fence.proxy.async.shared::cta;" ::: "memory");
            grid_arrive(4);
            DBG_STOP(4);
        }
    }
}

typedef CUresult (*EncodeFn)(CUtensorMap*, CUtensorMapDataType, cuuint32_t, void*, const cuuint64_t*, const cuuint64_t*,
                             const cuuint32_t*, const cuuint32_t*, CUtensorMapInterleave, CUtensorMapSwizzle,
                             CUtensorMapL2promotion, CUtensorMapFloatOOBfill);

CUtensorMap make_map(EncodeFn enc, void* ptr, int rank, const cuuint64_t* dims, const cuuint64_t* strides_bytes, const cuuint32_t* box,
                     CUtensorMapSwizzle swz = CU_TENSOR_MAP_SWIZZLE_128B) {
    CUtensorMap m;
    cuuint32_t es[3] = {1, 1, 1};
    enc(&m, CU_TENSOR_MAP_DATA_TYPE_BFLOAT16, rank, ptr, dims, strides_bytes, box, es, CU_TENSOR_MAP_INTERLEAVE_NONE,
        swz, CU_TENSOR_MAP_L2_PROMOTION_L2_128B, CU_TENSOR_MAP_FLOAT_OOB_FILL_NONE);
    return m;
}

}

extern "C" void kernel_launch(void* const* d_in, const int* in_sizes, int n_in, void* d_out, int out_size) {
    (void)in_sizes; (void)n_in; (void)out_size;
    static EncodeFn enc = nullptr;
    static void *p_h2 = nullptr, *p_u = nullptr;
    if (!enc) {
        void* fn = nullptr;
        cudaDriverEntryPointQueryResult qr;
        cudaGetDriverEntryPoint("cuTensorMapEncodeTiled", &fn, cudaEnableDefault, &qr);
        enc = (EncodeFn)fn;
        cudaGetSymbolAddress(&p_h2, g_h2);
        cudaGetSymbolAddress(&p_u, g_u);
        cudaFuncSetAttribute(fused_kernel, cudaFuncAttributeMaxDynamicSharedMemorySize, SM_TOTAL + 1024);
    }
    Params p;
    p.x = (const __nv_bfloat16*)d_in[0];
    p.w_r = (const __nv_bfloat16*)d_in[1];
    p.w_i = (const __nv_bfloat16*)d_in[2];
    p.w1 = (const __nv_bfloat16*)d_in[4];
    p.b1 = (const __nv_bfloat16*)d_in[5];
    p.w2 = (const __nv_bfloat16*)d_in[6];
    p.b2 = (const __nv_bfloat16*)d_in[7];
    p.c = (const __nv_bfloat16*)d_in[8];
    p.w_mod = (const __nv_bfloat16*)d_in[9];
    p.out = (__nv_bfloat16*)d_out;
    p.stop_after = 0;

    CUtensorMap tm_h2, tm_w1, tm_w2, tm_u, tm_wm, tm_x;
    {
        cuuint64_t dims[2] = {2048, 640}, str[1] = {H2P * 2};
        cuuint32_t box[2] = {64, 160};
        tm_h2 = make_map(enc, p_h2, 2, dims, str, box);
    }
    {
        cuuint64_t dims[3] = {1728, 16, 128}, str[2] = {(cuuint64_t)128 * 1728 * 2, 1728 * 2};
        cuuint32_t box[3] = {64, 16, 4};
        tm_w1 = make_map(enc, (void*)p.w1, 3, dims, str, box);
    }
    {
        cuuint64_t dims[2] = {2048, 1728}, str[1] = {2048 * 2};
        cuuint32_t box[2] = {64, 64};
        tm_w2 = make_map(enc, (void*)p.w2, 2, dims, str, box);
    }
    {
        cuuint64_t dims[2] = {1728, 640}, str[1] = {1728 * 2};
        cuuint32_t box[2] = {64, 160};
        tm_u = make_map(enc, p_u, 2, dims, str, box);
    }
    {
        cuuint64_t dims[2] = {3840, 640}, str[1] = {3840 * 2};
        cuuint32_t box[2] = {32, 128};
        tm_wm = make_map(enc, (void*)p.w_mod, 2, dims, str, box, CU_TENSOR_MAP_SWIZZLE_NONE);
    }
    {
        cuuint64_t dims[3] = {640, 16, 128}, str[2] = {(cuuint64_t)128 * 640 * 2, 640 * 2};
        cuuint32_t box[3] = {128, 16, 1};
        tm_x = make_map(enc, (void*)p.x, 3, dims, str, box, CU_TENSOR_MAP_SWIZZLE_NONE);
    }
    fused_kernel<<<NCTA, NT, SM_TOTAL + 1024, cudaStreamPerThread>>>(tm_h2, tm_w1, tm_w2, tm_u, tm_wm, tm_x, p);
}
```

```cpp
#include <cuda_runtime.h>
#include <cuda_bf16.h>
#include <cuda.h>
#include <stdint.h>

namespace {

constexpr int S_ = 2048, D_ = 640, F_ = 1728, DF_ = 321;
constexpr int NT = 320;
constexpr int NCTA = 132;

__device__ float2 g_buf[8 * 128 * 640];
__device__ float2 g_ext[2 * 128];
__device__ __align__(16) __nv_bfloat16 g_mod[6 * 640];
__device__ __align__(1024) __nv_bfloat16 g_x1[S_ * D_];
constexpr int H2P = S_ + 64;
__device__ __align__(1024) __nv_bfloat16 g_h2[D_ * H2P];
__device__ __align__(1024) __nv_bfloat16 g_u[D_ * F_];
__device__ unsigned int g_bar[8];
__device__ __align__(16) unsigned int g_modw[1280];
#define DBG_STOP(n)
#define TSTAMP(i)
#define TSTAMPT(i, T)
#define CLK(i)

__device__ __forceinline__ uint32_t smem_u32(const void* p) { return (uint32_t)__cvta_generic_to_shared(p); }
__device__ __forceinline__ float bf16r(float x) { return __bfloat162float(__float2bfloat16_rn(x)); }
__device__ __forceinline__ float bf_lo(uint32_t v) { return __uint_as_float(v << 16); }
__device__ __forceinline__ float bf_hi(uint32_t v) { return __uint_as_float(v & 0xffff0000u); }
__device__ __forceinline__ uint32_t pack_bf16(float lo, float hi) {
    uint32_t r;
    asm("cvt.rn.bf16x2.f32 %0, %1, %2;" : "=r"(r) : "f"(hi), "f"(lo));
    return r;
}
__device__ __forceinline__ float2 cmul(float2 a, float2 b) {
    return make_float2(fmaf(a.x, b.x, -a.y * b.y), fmaf(a.x, b.y, a.y * b.x));
}
__device__ __forceinline__ float2 cmulc(float2 a, float2 b) {
    return make_float2(fmaf(a.x, b.x, a.y * b.y), fmaf(a.y, b.x, -a.x * b.y));
}
__device__ __forceinline__ float2 cadd(float2 a, float2 b) { return make_float2(a.x + b.x, a.y + b.y); }
__device__ __forceinline__ float2 csub(float2 a, float2 b) { return make_float2(a.x - b.x, a.y - b.y); }

template <int DIR>
__device__ __forceinline__ float2 mul_i(float2 a) {
    return DIR > 0 ? make_float2(-a.y, a.x) : make_float2(a.y, -a.x);
}
template <int DIR>
__device__ __forceinline__ void fft4(float2& a0, float2& a1, float2& a2, float2& a3) {
    float2 t0 = cadd(a0, a2), t1 = csub(a0, a2), t2 = cadd(a1, a3), t3 = mul_i<DIR>(csub(a1, a3));
    a0 = cadd(t0, t2); a2 = csub(t0, t2); a1 = cadd(t1, t3); a3 = csub(t1, t3);
}
template <int DIR>
__device__ __forceinline__ float2 mul_w8_1(float2 a) {
    const float c = 0.70710678118654752440f;
    return DIR > 0 ? make_float2((a.x - a.y) * c, (a.x + a.y) * c) : make_float2((a.x + a.y) * c, (a.y - a.x) * c);
}
template <int DIR>
__device__ __forceinline__ float2 mul_w8_3(float2 a) {
    const float c = 0.70710678118654752440f;
    return DIR > 0 ? make_float2(-(a.x + a.y) * c, (a.x - a.y) * c) : make_float2((a.y - a.x) * c, -(a.x + a.y) * c);
}
template <int DIR>
__device__ __forceinline__ float2 mul_cs(float2 a, float c, float s) {
    return DIR > 0 ? make_float2(fmaf(a.x, c, -a.y * s), fmaf(a.y, c, a.x * s))
                   : make_float2(fmaf(a.x, c, a.y * s), fmaf(a.y, c, -a.x * s));
}
template <int DIR>
__device__ __forceinline__ void fft8(float2 (&v)[8]) {
    fft4<DIR>(v[0], v[2], v[4], v[6]);
    fft4<DIR>(v[1], v[3], v[5], v[7]);
    float2 o1 = mul_w8_1<DIR>(v[3]), o2 = mul_i<DIR>(v[5]), o3 = mul_w8_3<DIR>(v[7]), o0 = v[1];
    float2 e0 = v[0], e1 = v[2], e2 = v[4], e3 = v[6];
    v[0] = cadd(e0, o0); v[4] = csub(e0, o0);
    v[1] = cadd(e1, o1); v[5] = csub(e1, o1);
    v[2] = cadd(e2, o2); v[6] = csub(e2, o2);
    v[3] = cadd(e3, o3); v[7] = csub(e3, o3);
}
template <int DIR>
__device__ __forceinline__ void fft16(float2 (&v)[16]) {
    const float c1 = 0.92387953251128675613f, s1 = 0.38268343236508977173f;
#pragma unroll
    for (int n2 = 0; n2 < 4; n2++) fft4<DIR>(v[n2], v[4 + n2], v[8 + n2], v[12 + n2]);
    v[5] = mul_cs<DIR>(v[5], c1, s1);
    v[6] = mul_w8_1<DIR>(v[6]);
    v[7] = mul_cs<DIR>(v[7], s1, c1);
    v[9] = mul_w8_1<DIR>(v[9]);
    v[10] = mul_i<DIR>(v[10]);
    v[11] = mul_w8_3<DIR>(v[11]);
    v[13] = mul_cs<DIR>(v[13], s1, c1);
    v[14] = mul_w8_3<DIR>(v[14]);
    v[15] = mul_cs<DIR>(v[15], -c1, -s1);
#pragma unroll
    for (int k1 = 0; k1 < 4; k1++) fft4<DIR>(v[4 * k1], v[4 * k1 + 1], v[4 * k1 + 2], v[4 * k1 + 3]);
    float2 t;
#define SWP(a, b) t = v[a]; v[a] = v[b]; v[b] = t;
    SWP(1, 4) SWP(2, 8) SWP(3, 12) SWP(6, 9) SWP(7, 13) SWP(11, 14)
#undef SWP
}
template <int DIR>
__device__ __forceinline__ void fft5(float2& x0, float2& x1, float2& x2, float2& x3, float2& x4) {
    const float c1 = 0.30901699437494742410f, c2 = -0.80901699437494742410f;
    const float s1 = 0.95105651629515357212f, s2 = 0.58778525229247312917f;
    float2 t1 = cadd(x1, x4), t2 = cadd(x2, x3), t3 = csub(x1, x4), t4 = csub(x2, x3);
    float2 a1 = make_float2(fmaf(c2, t2.x, fmaf(c1, t1.x, x0.x)), fmaf(c2, t2.y, fmaf(c1, t1.y, x0.y)));
    float2 a2 = make_float2(fmaf(c1, t2.x, fmaf(c2, t1.x, x0.x)), fmaf(c1, t2.y, fmaf(c2, t1.y, x0.y)));
    float2 b1 = make_float2(fmaf(s2, t4.x, s1 * t3.x), fmaf(s2, t4.y, s1 * t3.y));
    float2 b2 = make_float2(fmaf(-s1, t4.x, s2 * t3.x), fmaf(-s1, t4.y, s2 * t3.y));
    x0 = make_float2(x0.x + t1.x + t2.x, x0.y + t1.y + t2.y);
    float2 ib1 = mul_i<DIR>(b1), ib2 = mul_i<DIR>(b2);
    x1 = cadd(a1, ib1); x4 = csub(a1, ib1);
    x2 = cadd(a2, ib2); x3 = csub(a2, ib2);
}
template <int DIR>
__device__ __forceinline__ void fft20(float2 (&v)[20]) {
    float2 t[4][5];
#pragma unroll
    for (int n1 = 0; n1 < 4; n1++)
#pragma unroll
        for (int n2 = 0; n2 < 5; n2++) t[n1][n2] = v[(5 * n1 + 4 * n2) % 20];
#pragma unroll
    for (int n1 = 0; n1 < 4; n1++) fft5<DIR>(t[n1][0], t[n1][1], t[n1][2], t[n1][3], t[n1][4]);
#pragma unroll
    for (int k2 = 0; k2 < 5; k2++) fft4<DIR>(t[0][k2], t[1][k2], t[2][k2], t[3][k2]);
#pragma unroll
    for (int k1 = 0; k1 < 4; k1++)
#pragma unroll
        for (int k2 = 0; k2 < 5; k2++) v[(5 * k1 + 16 * k2) % 20] = t[k1][k2];
}

__device__ __forceinline__ void mbar_init(uint32_t a, uint32_t c) { asm volatile("mbarrier.init.shared::cta.b64 [%0], %1;" ::"r"(a), "r"(c)); }
__device__ __forceinline__ void mbar_expect(uint32_t a, uint32_t b) {
    asm volatile("mbarrier.arrive.expect_tx.shared::cta.b64 _, [%0], %1;" ::"r"(a), "r"(b) : "memory");
}
__device__ __forceinline__ void mbar_arrive(uint32_t a) { asm volatile("mbarrier.arrive.shared::cta.b64 _, [%0];" ::"r"(a) : "memory"); }
__device__ __forceinline__ uint32_t mbar_try(uint32_t a, uint32_t ph) {
    uint32_t ok;
    asm volatile("{\n.reg .pred p;\nmbarrier.try_wait.parity.shared::cta.b64 p, [%1], %2;\nselp.u32 %0, 1, 0, p;\n}"
                 : "=r"(ok) : "r"(a), "r"(ph) : "memory");
    return ok;
}
__device__ __forceinline__ void mbar_wait(uint32_t a, uint32_t ph) {
    if (mbar_try(a, ph)) return;
    int it = 0;
    while (!mbar_try(a, ph)) { if (++it > 4000000) __trap(); }
}
__device__ __forceinline__ uint32_t elect_one() {
    uint32_t pred;
    asm volatile("{\n.reg .pred p;\nelect.sync _|p, 0xffffffff;\nselp.u32 %0, 1, 0, p;\n}" : "=r"(pred));
    return pred;
}
__device__ __forceinline__ void tma2d(uint32_t dst, const CUtensorMap* m, int c0, int c1, uint32_t bar) {
    asm volatile("cp.async.bulk.tensor.2d.shared::cluster.global.mbarrier::complete_tx::bytes [%0], [%1, {%3, %4}], [%2];"
                 ::"r"(dst), "l"(m), "r"(bar), "r"(c0), "r"(c1) : "memory");
}
__device__ __forceinline__ void tma3d(uint32_t dst, const CUtensorMap* m, int c0, int c1, int c2, uint32_t bar) {
    asm volatile("cp.async.bulk.tensor.3d.shared::cluster.global.mbarrier::complete_tx::bytes [%0], [%1, {%3, %4, %5}], [%2];"
                 ::"r"(dst), "l"(m), "r"(bar), "r"(c0), "r"(c1), "r"(c2) : "memory");
}
__device__ __forceinline__ uint64_t make_desc(uint32_t addr, uint32_t lbo, uint32_t sbo) {
    uint64_t d = 0;
    d |= (uint64_t)((addr & 0x3FFFF) >> 4);
    d |= (uint64_t)((lbo >> 4) & 0x3FFF) << 16;
    d |= (uint64_t)((sbo >> 4) & 0x3FFF) << 32;
    d |= (uint64_t)1 << 62;
    return d;
}
#define WG_FENCE() asm volatile("wgmma.fence.sync.aligned;" ::: "memory")
#define WG_COMMIT() asm volatile("wgmma.commit_group.sync.aligned;" ::: "memory")
template <int N>
__device__ __forceinline__ void wg_wait() { asm volatile("wgmma.wait_group.sync.aligned %0;" ::"n"(N) : "memory"); }

__device__ __forceinline__ void wgmma_tn_160(float (&d)[80], uint64_t da, uint64_t db, int scale_d) {
    asm volatile("{\n.reg .pred p;\nsetp.ne.b32 p, %82, 0;\n"
        "wgmma.mma_async.sync.aligned.m64n160k16.f32.bf16.bf16 {%0, %1, %2, %3, %4, %5, %6, %7, %8, %9, %10, %11, %12, %13, %14, %15, %16, %17, %18, %19, %20, %21, %22, %23, %24, %25, %26, %27, %28, %29, %30, %31, %32, %33, %34, %35, %36, %37, %38, %39, %40, %41, %42, %43, %44, %45, %46, %47, %48, %49, %50, %51, %52, %53, %54, %55, %56, %57, %58, %59, %60, %61, %62, %63, %64, %65, %66, %67, %68, %69, %70, %71, %72, %73, %74, %75, %76, %77, %78, %79}, %80, %81, p, 1, 1, 1, 0;\n}\n"
        : "+f"(d[0]), "+f"(d[1]), "+f"(d[2]), "+f"(d[3]), "+f"(d[4]), "+f"(d[5]), "+f"(d[6]), "+f"(d[7]), "+f"(d[8]), "+f"(d[9]), "+f"(d[10]), "+f"(d[11]), "+f"(d[12]), "+f"(d[13]), "+f"(d[14]), "+f"(d[15]), "+f"(d[16]), "+f"(d[17]), "+f"(d[18]), "+f"(d[19]), "+f"(d[20]), "+f"(d[21]), "+f"(d[22]), "+f"(d[23]), "+f"(d[24]), "+f"(d[25]), "+f"(d[26]), "+f"(d[27]), "+f"(d[28]), "+f"(d[29]), "+f"(d[30]), "+f"(d[31]), "+f"(d[32]), "+f"(d[33]), "+f"(d[34]), "+f"(d[35]), "+f"(d[36]), "+f"(d[37]), "+f"(d[38]), "+f"(d[39]), "+f"(d[40]), "+f"(d[41]), "+f"(d[42]), "+f"(d[43]), "+f"(d[44]), "+f"(d[45]), "+f"(d[46]), "+f"(d[47]), "+f"(d[48]), "+f"(d[49]), "+f"(d[50]), "+f"(d[51]), "+f"(d[52]), "+f"(d[53]), "+f"(d[54]), "+f"(d[55]), "+f"(d[56]), "+f"(d[57]), "+f"(d[58]), "+f"(d[59]), "+f"(d[60]), "+f"(d[61]), "+f"(d[62]), "+f"(d[63]), "+f"(d[64]), "+f"(d[65]), "+f"(d[66]), "+f"(d[67]), "+f"(d[68]), "+f"(d[69]), "+f"(d[70]), "+f"(d[71]), "+f"(d[72]), "+f"(d[73]), "+f"(d[74]), "+f"(d[75]), "+f"(d[76]), "+f"(d[77]), "+f"(d[78]), "+f"(d[79])
        : "l"(da), "l"(db), "r"(scale_d));
}

__device__ __forceinline__ void red_release(unsigned int* p) {
    asm volatile("red.release.gpu.global.add.u32 [%0], 1;" ::"l"(p) : "memory");
}
__device__ __forceinline__ unsigned int ld_relaxed(const unsigned int* p) {
    unsigned int v;
    asm volatile("ld.relaxed.gpu.global.u32 %0, [%1];" : "=r"(v) : "l"(p) : "memory");
    return v;
}
__device__ __forceinline__ void spin_until(const unsigned int* p, unsigned int target) {
    int it = 0;
    while (ld_relaxed(p) < target) { if (++it > 20000000) __trap(); }
    unsigned int v;
    asm volatile("ld.acquire.gpu.global.u32 %0, [%1];" : "=r"(v) : "l"(p) : "memory");
}
__device__ __forceinline__ void grid_arrive(int k) {
    __syncthreads();
    if (threadIdx.x == 0) red_release(&g_bar[k]);
}
__device__ __forceinline__ void grid_wait(int k, unsigned int target) {
    if (threadIdx.x == 0) spin_until(&g_bar[k], target);
    __syncthreads();
}

constexpr int SM_STAGE_BYTES = 172032;
constexpr int SM_WF = 90112;
constexpr int SM_OT = 114688;
constexpr int SM_WMOD = 131072;
constexpr int G_STAGES = 6, G_STAGE_BYTES = 8192 + 20480;
constexpr int SM_T1 = SM_STAGE_BYTES;
constexpr int SM_T3 = SM_T1 + 5120;
constexpr int SM_T2 = SM_T3 + 5120;
constexpr int SM_TA = SM_T2 + 1024;
constexpr int SM_RED = SM_TA + 1152;
constexpr int SM_SILU = SM_RED + 1280;
constexpr int SM_BARS = SM_SILU + 2560;
constexpr int SM_MODV = SM_BARS + 512;
constexpr int SM_X = SM_MODV + 3840;
constexpr int SM_TOTAL = SM_X + 20480;

struct Params {
    const __nv_bfloat16* x;
    const __nv_bfloat16* w_r;
    const __nv_bfloat16* w_i;
    const __nv_bfloat16* w1;
    const __nv_bfloat16* b1;
    const __nv_bfloat16* w2;
    const __nv_bfloat16* b2;
    const __nv_bfloat16* c;
    const __nv_bfloat16* w_mod;
    __nv_bfloat16* out;
    int stop_after;
};

__device__ __forceinline__ uint32_t badd(uint32_t a, uint32_t b) { uint32_t r; asm("add.rn.bf16x2 %0, %1, %2;" : "=r"(r) : "r"(a), "r"(b)); return r; }
__device__ __forceinline__ uint32_t bsub(uint32_t a, uint32_t b) { uint32_t r; asm("sub.rn.bf16x2 %0, %1, %2;" : "=r"(r) : "r"(a), "r"(b)); return r; }
__device__ __forceinline__ uint32_t bmul(uint32_t a, uint32_t b) { uint32_t r; asm("mul.rn.bf16x2 %0, %1, %2;" : "=r"(r) : "r"(a), "r"(b)); return r; }
__device__ __forceinline__ uint4 ldg128(const void* p) { return __ldg(reinterpret_cast<const uint4*>(p)); }
__device__ __forceinline__ uint4 ldcg128(const void* p) {
    uint4 v;
    asm volatile("ld.global.cg.v4.u32 {%0,%1,%2,%3}, [%4];" : "=r"(v.x), "=r"(v.y), "=r"(v.z), "=r"(v.w) : "l"(p));
    return v;
}
__device__ __forceinline__ void stg128(void* p, uint32_t a, uint32_t b, uint32_t c, uint32_t d) {
    asm volatile("st.global.v4.u32 [%0], {%1,%2,%3,%4};" ::"l"(p), "r"(a), "r"(b), "r"(c), "r"(d) : "memory");
}
__device__ __forceinline__ float2 ldcg64(const float2* p) {
    float2 v;
    asm volatile("ld.global.cg.v2.f32 {%0,%1}, [%2];" : "=f"(v.x), "=f"(v.y) : "l"(p));
    return v;
}

__device__ __forceinline__ void ln_row(uint32_t (&w)[20]) {
    float sa[4] = {0.f, 0.f, 0.f, 0.f};
#pragma unroll
    for (int i = 0; i < 20; i += 2) { sa[0] += bf_lo(w[i]); sa[1] += bf_hi(w[i]); sa[2] += bf_lo(w[i + 1]); sa[3] += bf_hi(w[i + 1]); }
    float s = (sa[0] + sa[1]) + (sa[2] + sa[3]);
#pragma unroll
    for (int m = 8; m >= 1; m >>= 1) s += __shfl_xor_sync(0xffffffffu, s, m);
    const float mu = s * (1.0f / 640.0f);
    float qa[4] = {0.f, 0.f, 0.f, 0.f};
#pragma unroll
    for (int i = 0; i < 20; i += 2) {
        const float d0 = bf_lo(w[i]) - mu, d1 = bf_hi(w[i]) - mu, d2 = bf_lo(w[i + 1]) - mu, d3 = bf_hi(w[i + 1]) - mu;
        qa[0] = fmaf(d0, d0, qa[0]); qa[1] = fmaf(d1, d1, qa[1]); qa[2] = fmaf(d2, d2, qa[2]); qa[3] = fmaf(d3, d3, qa[3]);
    }
    float q = (qa[0] + qa[1]) + (qa[2] + qa[3]);
#pragma unroll
    for (int m = 8; m >= 1; m >>= 1) q += __shfl_xor_sync(0xffffffffu, q, m);
    const float var = bf16r(q * (1.0f / 640.0f));
    const float den = bf16r(sqrtf(bf16r(var + 1e-5f)));
    const float r = __fdiv_rn(1.0f, den);
    const uint32_t m2 = pack_bf16(mu, mu);
#pragma unroll
    for (int i = 0; i < 20; i++) {
        const uint32_t d = bsub(w[i], m2);
        w[i] = pack_bf16(bf_lo(d) * r, bf_hi(d) * r);
    }
}
__device__ __forceinline__ void unpack4(uint32_t* w, uint4 v) { w[0] = v.x; w[1] = v.y; w[2] = v.z; w[3] = v.w; }

__device__ __forceinline__ void gemm_consumer(float (&acc)[80], uint32_t sm_base_u, uint32_t fullb, int NK, int tid) {
    const uint32_t emptyb = fullb + 64;
    const uint64_t da0 = make_desc(sm_base_u, 8192, 1024);
    const uint64_t db0 = make_desc(sm_base_u + 8192, 16, 1024);
    uint32_t ph = 0;
    mbar_wait(fullb, 0);
#pragma unroll 1
    for (int kb0 = 0; kb0 < NK; kb0 += G_STAGES) {
#pragma unroll
        for (int s = 0; s < G_STAGES; s++) {
            const int kb = kb0 + s;
            if (kb < NK) {
                constexpr uint64_t one = 1;
                const uint64_t so = one * ((s * G_STAGE_BYTES) >> 4);
                WG_FENCE();
#pragma unroll
                for (int k = 0; k < 4; k++) wgmma_tn_160(acc, da0 + so + k * 128, db0 + so + k * 2, (kb > 0 || k > 0) ? 1 : 0);
                WG_COMMIT();
                const int sn = (s + 1) % G_STAGES;
                if (kb + 1 < NK) mbar_wait(fullb + 8 * sn, (s + 1 == G_STAGES) ? ph ^ 1 : ph);
                wg_wait<1>();
                if (kb > 0 && tid == 0) mbar_arrive(emptyb + 8 * ((s + G_STAGES - 1) % G_STAGES));
            }
        }
        ph ^= 1;
    }
}

__device__ __forceinline__ void load_wmod_slab(const CUtensorMap* tm, uint32_t dst, int cta, uint32_t bar) {
    mbar_expect(bar, 640 * 64);
#pragma unroll
    for (int i = 0; i < 5; i++) tma2d(dst + i * 128 * 64, tm, cta * 32, i * 128, bar);
}
__device__ __forceinline__ void mod_partial(const unsigned char* slab, const float* s_silu, float* s_red, int tid) {
    uint4 wm[8];
#pragma unroll
    for (int i = 0; i < 8; i++) wm[i] = *reinterpret_cast<const uint4*>(slab + ((tid >> 2) + 80 * i) * 64 + (tid & 3) * 16);
    float acc[8];
#pragma unroll
    for (int e = 0; e < 8; e++) acc[e] = 0.f;
#pragma unroll
    for (int i = 0; i < 8; i++) {
        const float sv = s_silu[(tid >> 2) + 80 * i];
        acc[0] = fmaf(sv, bf_lo(wm[i].x), acc[0]); acc[1] = fmaf(sv, bf_hi(wm[i].x), acc[1]);
        acc[2] = fmaf(sv, bf_lo(wm[i].y), acc[2]); acc[3] = fmaf(sv, bf_hi(wm[i].y), acc[3]);
        acc[4] = fmaf(sv, bf_lo(wm[i].z), acc[4]); acc[5] = fmaf(sv, bf_hi(wm[i].z), acc[5]);
        acc[6] = fmaf(sv, bf_lo(wm[i].w), acc[6]); acc[7] = fmaf(sv, bf_hi(wm[i].w), acc[7]);
    }
    const int lane = tid & 31;
    const bool u16 = lane & 16, u8 = lane & 8, u4 = lane & 4;
    float b4[4], b2[2], b1;
#pragma unroll
    for (int e = 0; e < 4; e++) {
        const float keep = u16 ? acc[e + 4] : acc[e], send = u16 ? acc[e] : acc[e + 4];
        b4[e] = keep + __shfl_xor_sync(0xffffffffu, send, 16);
    }
#pragma unroll
    for (int e = 0; e < 2; e++) {
        const float keep = u8 ? b4[e + 2] : b4[e], send = u8 ? b4[e] : b4[e + 2];
        b2[e] = keep + __shfl_xor_sync(0xffffffffu, send, 8);
    }
    {
        const float keep = u4 ? b2[1] : b2[0], send = u4 ? b2[0] : b2[1];
        b1 = keep + __shfl_xor_sync(0xffffffffu, send, 4);
    }
    s_red[(tid >> 5) * 32 + (lane & 3) * 8 + (u16 ? 4 : 0) + (u8 ? 2 : 0) + (u4 ? 1 : 0)] = b1;
}

__device__ __forceinline__ void prefetch_chunk(const void* base, int cta, int half, int tid) {
    if (tid == 288 && cta < 128)
        asm volatile("cp.async.bulk.prefetch.L2.global [%0], %1;" ::"l"((const char*)base + (cta * 2 + half) * 27648), "r"(27648));
}

__global__ void __launch_bounds__(NT, 1)
fused_kernel(const __grid_constant__ CUtensorMap tm_h2, const __grid_constant__ CUtensorMap tm_w1,
             const __grid_constant__ CUtensorMap tm_w2, const __grid_constant__ CUtensorMap tm_u,
             const __grid_constant__ CUtensorMap tm_wm, const __grid_constant__ CUtensorMap tm_x, const Params p) {
    extern __shared__ unsigned char sm_raw[];
    const uint32_t sm_base_u = __shfl_sync(0xffffffffu, (smem_u32(sm_raw) + 1023u) & ~1023u, 0);
    unsigned char* sm = sm_raw + (sm_base_u - smem_u32(sm_raw));
    float2* s_t1 = reinterpret_cast<float2*>(sm + SM_T1);
    float2* s_t3 = reinterpret_cast<float2*>(sm + SM_T3);
    float2* s_t2 = reinterpret_cast<float2*>(sm + SM_T2);
    float2* s_ta = reinterpret_cast<float2*>(sm + SM_TA);
    float* s_red = reinterpret_cast<float*>(sm + SM_RED);
    const uint32_t bars = sm_base_u + SM_BARS;

    const int tid = threadIdx.x, lane = tid & 31;
    const int warp = __shfl_sync(0xffffffffu, tid >> 5, 0);
    const int cta = blockIdx.x;
    const int s0 = cta;
    const int lrow = 2 * warp + (lane >> 4);
    const int ll = lane & 15;
    TSTAMP(0);

    float* s_silu = reinterpret_cast<float*>(sm + SM_SILU);
    const uint32_t bar_x = bars + 256, bar_w = bars + 264;
    if (tid == 288) {
        for (int i = 0; i < 8; i++) { mbar_init(bars + 8 * i, 1); mbar_init(bars + 64 + 8 * i, 1); mbar_init(bars + 128 + 8 * i, 1); mbar_init(bars + 192 + 8 * i, 1); }
        mbar_init(bar_x, 1); mbar_init(bar_w, 1);
        asm volatile("fence.mbarrier_init.release.cluster;" ::: "memory");
        if (cta < 40) load_wmod_slab(&tm_wm, sm_base_u + SM_WMOD, cta, bar_w);
        if (cta == 0) g_bar[4] = 0;
        __nanosleep(400);
        if (cta < 128) {
            mbar_expect(bar_x, 16 * 1280);
#pragma unroll
            for (int i = 0; i < 5; i++) tma3d(sm_base_u + SM_X + i * 4096, &tm_x, i * 128, 0, s0, bar_x);
        }
    }
    uint4 cvv = make_uint4(0, 0, 0, 0);
    if (tid >= 208 && tid < 288) cvv = ldg128(p.c + (tid - 208) * 8);
    uint32_t xw[20];
    TSTAMP(17);
#pragma unroll 1
    for (int i = tid; i < 1552 && tid < 288; i += 288) {
        float ang;
        if (i < 640) ang = (float)((i % 80) * (i / 80)) * (1.0f / 320.0f);
        else if (i < 1280) ang = (float)(((i - 640) & 31) * ((i - 640) >> 5)) * (1.0f / 320.0f);
        else if (i < 1408) ang = (float)(((i - 1280) & 15) * ((i - 1280) >> 4)) * (1.0f / 64.0f);
        else ang = (float)(((128 * ((i - 1408) & 15) + s0) * ((i - 1408) >> 4)) & 2047) * (1.0f / 1024.0f);
        float s, c;
        sincospif(-ang, &s, &c);
        s_t1[i] = make_float2(c, s);
    }
    if (tid >= 208 && tid < 288) {
        const uint32_t w4[4] = {cvv.x, cvv.y, cvv.z, cvv.w};
        float o[8];
#pragma unroll
        for (int e = 0; e < 4; e++) {
            const float c0 = bf_lo(w4[e]), c1 = bf_hi(w4[e]);
            o[2 * e] = bf16r(__fdividef(c0, 1.0f + exp2f(-1.4426950409f * c0)));
            o[2 * e + 1] = bf16r(__fdividef(c1, 1.0f + exp2f(-1.4426950409f * c1)));
        }
        *reinterpret_cast<float4*>(s_silu + (tid - 208) * 8) = make_float4(o[0], o[1], o[2], o[3]);
        *reinterpret_cast<float4*>(s_silu + (tid - 208) * 8 + 4) = make_float4(o[4], o[5], o[6], o[7]);
    }
    TSTAMP(18);
    __syncthreads();
    if (cta < 40 && warp >= 8) {
        mbar_wait(bar_w, 0);
        const int t6 = tid - 256, rg = t6 >> 2, cg = t6 & 3;
        float acc[8];
#pragma unroll
        for (int e = 0; e < 8; e++) acc[e] = 0.f;
#pragma unroll 8
        for (int i = 0; i < 40; i++) {
            const uint4 w = *reinterpret_cast<const uint4*>(sm + SM_WMOD + (rg + 16 * i) * 64 + cg * 16);
            const float sv = s_silu[rg + 16 * i];
            acc[0] = fmaf(sv, bf_lo(w.x), acc[0]); acc[1] = fmaf(sv, bf_hi(w.x), acc[1]);
            acc[2] = fmaf(sv, bf_lo(w.y), acc[2]); acc[3] = fmaf(sv, bf_hi(w.y), acc[3]);
            acc[4] = fmaf(sv, bf_lo(w.z), acc[4]); acc[5] = fmaf(sv, bf_hi(w.z), acc[5]);
            acc[6] = fmaf(sv, bf_lo(w.w), acc[6]); acc[7] = fmaf(sv, bf_hi(w.w), acc[7]);
        }
        const bool u16 = lane & 16, u8 = lane & 8, u4 = lane & 4;
        float b4[4], b2[2], b1;
#pragma unroll
        for (int e = 0; e < 4; e++) {
            const float keep = u16 ? acc[e + 4] : acc[e], send = u16 ? acc[e] : acc[e + 4];
            b4[e] = keep + __shfl_xor_sync(0xffffffffu, send, 16);
        }
#pragma unroll
        for (int e = 0; e < 2; e++) {
            const float keep = u8 ? b4[e + 2] : b4[e], send = u8 ? b4[e] : b4[e + 2];
            b2[e] = keep + __shfl_xor_sync(0xffffffffu, send, 8);
        }
        {
            const float keep = u4 ? b2[1] : b2[0], send = u4 ? b2[0] : b2[1];
            b1 = keep + __shfl_xor_sync(0xffffffffu, send, 4);
        }
        s_red[(warp - 8) * 32 + (lane & 3) * 8 + (u16 ? 4 : 0) + (u8 ? 2 : 0) + (u4 ? 1 : 0)] = b1;
        asm volatile("bar.sync 3, 64;" ::: "memory");
        if (warp == 9) {
            const float t = s_red[lane] + s_red[32 + lane];
            asm volatile("st.relaxed.gpu.global.u32 [%0], %1;" ::"l"(&g_modw[cta * 32 + lane]), "r"(0x80000000u | (pack_bf16(t, 0.f) & 0xffffu)) : "memory");
            TSTAMPT(23, 288);
        }
    }
    if (tid == 288) {
        const uint32_t cW = 9968;
        const uint32_t off = cta * cW, n = min(cW, 1314816u - min(off, 1314816u));
        if (n) {
            asm volatile("cp.async.bulk.prefetch.L2.global [%0], %1;" ::"l"((const char*)p.w_r + off), "r"(n));
            asm volatile("cp.async.bulk.prefetch.L2.global [%0], %1;" ::"l"((const char*)p.w_i + off), "r"(n));
        }
        if (cta >= 40 && cta < 120) load_wmod_slab(&tm_wm, sm_base_u + SM_WMOD, cta, bar_w);
        asm volatile("prefetch.tensormap [%0];" ::"l"(&tm_h2) : "memory");
        asm volatile("prefetch.tensormap [%0];" ::"l"(&tm_w1) : "memory");
        asm volatile("prefetch.tensormap [%0];" ::"l"(&tm_w2) : "memory");
        asm volatile("prefetch.tensormap [%0];" ::"l"(&tm_u) : "memory");
    }

    if (cta == 128 && tid < 256) {
        const int q = 8 * (tid >> 7), ks = q + 16 * (tid & 127), ksm = (2048 - ks) & 2047;
        reinterpret_cast<float2*>(sm + SM_WF)[tid] =
            make_float2(0.5f * (__bfloat162float(__ldg(p.w_r + ks * DF_ + 320)) + __bfloat162float(__ldg(p.w_r + ksm * DF_ + 320))),
                        0.5f * (__bfloat162float(__ldg(p.w_i + ks * DF_ + 320)) - __bfloat162float(__ldg(p.w_i + ksm * DF_ + 320))));
    }

    if (cta < 128) {
        uint32_t afr[3][4];
        {
            const int g = lane >> 2, t = lane & 3;
            const float scale = 1.0f / (2048.0f * 640.0f);
            float cr[4], ci[4];
#pragma unroll
            for (int i = 0; i < 4; i++) {
                const int j = 2 * t + (i & 1) + (i >> 1) * 8;
                const float2 w = s_ta[g * 16 + j];
                cr[i] = w.x * scale;
                ci[i] = (g == 0 ? ((i & 1) ? -1.0f : 1.0f) : w.y) * scale;
            }
#pragma unroll
            for (int l = 0; l < 3; l++) {
                afr[l][0] = pack_bf16(cr[0], cr[1]);
                afr[l][1] = pack_bf16(ci[0], ci[1]);
                afr[l][2] = pack_bf16(cr[2], cr[3]);
                afr[l][3] = pack_bf16(ci[2], ci[3]);
                cr[0] -= bf_lo(afr[l][0]); cr[1] -= bf_hi(afr[l][0]); ci[0] -= bf_lo(afr[l][1]); ci[1] -= bf_hi(afr[l][1]);
                cr[2] -= bf_lo(afr[l][2]); cr[3] -= bf_hi(afr[l][2]); ci[2] -= bf_lo(afr[l][3]); ci[3] -= bf_hi(afr[l][3]);
            }
        }
        if (warp < 8) {
            mbar_wait(bar_x, 0);
#pragma unroll
            for (int i = 0; i < 5; i++) unpack4(xw + 4 * i, *reinterpret_cast<const uint4*>(sm + SM_X + i * 4096 + lrow * 256 + ll * 16));
            ln_row(xw);
            TSTAMP(1);
        } else {
            {
                const int t6 = tid - 256;
                uint4 a[3], b[3];
                int it = 0;
                unsigned ok;
                do {
                    ok = 0x80000000u;
#pragma unroll
                    for (int i = 0; i < 3; i++) {
                        const int c = min(t6 + 64 * i, 159);
                        asm volatile("ld.relaxed.gpu.global.v4.u32 {%0,%1,%2,%3}, [%4];" : "=r"(a[i].x), "=r"(a[i].y), "=r"(a[i].z), "=r"(a[i].w) : "l"(g_modw + c * 8) : "memory");
                        asm volatile("ld.relaxed.gpu.global.v4.u32 {%0,%1,%2,%3}, [%4];" : "=r"(b[i].x), "=r"(b[i].y), "=r"(b[i].z), "=r"(b[i].w) : "l"(g_modw + c * 8 + 4) : "memory");
                    }
#pragma unroll
                    for (int i = 0; i < 3; i++) ok &= a[i].x & a[i].y & a[i].z & a[i].w & b[i].x & b[i].y & b[i].z & b[i].w;
                    if (++it > 20000000) __trap();
                } while ((ok >> 31) == 0);
#pragma unroll
                for (int i = 0; i < 3; i++) {
                    const int c = t6 + 64 * i;
                    if (c < 160)
                        *reinterpret_cast<uint4*>(sm + SM_MODV + c * 16) =
                            make_uint4(__byte_perm(a[i].x, a[i].y, 0x5410), __byte_perm(a[i].z, a[i].w, 0x5410), __byte_perm(b[i].x, b[i].y, 0x5410), __byte_perm(b[i].z, b[i].w, 0x5410));
                }
            }
            prefetch_chunk(p.w1, cta, 0, tid);
            if ((cta & 7) == 0) {
                const int r = cta >> 4, b = cta & 15;
                const int q = r ? r : ((b < 8) ? 0 : 8);
                const bool cj = r && b >= 8;
                const int kc = cj ? 320 : 0;
#pragma unroll
                for (int i = 0; i < 2; i++) {
                    const int pp = tid - 256 + 64 * i, ks = q + 16 * pp;
                    const int orow = cj ? ks : ((2048 - ks) & 2047);
                    reinterpret_cast<float2*>(sm + SM_OT)[pp] =
                        make_float2(__bfloat162float(__ldg(p.w_r + orow * DF_ + kc)), __bfloat162float(__ldg(p.w_i + orow * DF_ + kc)));
                }
            }
        }
        __syncthreads();
        TSTAMP(2);
        CLK(0);

        if (warp < 8) {
            uint4 sa[5], ca[5];
#pragma unroll
            for (int i = 0; i < 5; i++) {
                sa[i] = *reinterpret_cast<const uint4*>(sm + SM_MODV + (ll + 16 * i) * 16);
                ca[i] = *reinterpret_cast<const uint4*>(sm + SM_MODV + 1280 + (ll + 16 * i) * 16);
            }
            const uint32_t one2 = 0x3f803f80u;
#pragma unroll
            for (int i = 0; i < 5; i++) {
                uint4 h;
                h.x = badd(bmul(xw[4 * i + 0], badd(one2, ca[i].x)), sa[i].x);
                h.y = badd(bmul(xw[4 * i + 1], badd(one2, ca[i].y)), sa[i].y);
                h.z = badd(bmul(xw[4 * i + 2], badd(one2, ca[i].z)), sa[i].z);
                h.w = badd(bmul(xw[4 * i + 3], badd(one2, ca[i].w)), sa[i].w);
                *reinterpret_cast<uint4*>(sm + lrow * 1296 + (ll + 16 * i) * 16) = h;
            }
        }
        CLK(1);
        __syncthreads();
        CLK(2);
        float2* s_f = reinterpret_cast<float2*>(sm + 24576);
        constexpr int PB2 = 24, PK = 121, PR = 968;
        {
            const int g = lane >> 2, t = lane & 3;
            float2 z0[8], z1[8];
            const uint32_t laddr = sm_base_u + (((lane >> 3) & 1) * 8 + (lane & 7)) * 1296 + (80 * (lane >> 4) + 8 * warp) * 2;
#pragma unroll
            for (int ap = 0; ap < 4; ap++) {
                uint32_t b0, b1, b2, b3;
                asm volatile("ldmatrix.sync.aligned.m8n8.x4.trans.shared.b16 {%0,%1,%2,%3}, [%4];"
                             : "=r"(b0), "=r"(b1), "=r"(b2), "=r"(b3) : "r"(laddr + ap * 320));
#pragma unroll
                for (int h = 0; h < 2; h++) {
                    float c0 = 0.f, c1 = 0.f, c2 = 0.f, c3 = 0.f;
                    const uint32_t bb0 = h ? b2 : b0, bb1 = h ? b3 : b1;
#pragma unroll
                    for (int l = 2; l >= 0; l--) {
                        asm volatile("mma.sync.aligned.m16n8k16.row.col.f32.bf16.bf16.f32 {%0,%1,%2,%3}, {%4,%5,%6,%7}, {%8,%9}, {%0,%1,%2,%3};"
                                     : "+f"(c0), "+f"(c1), "+f"(c2), "+f"(c3)
                                     : "r"(afr[l][0]), "r"(afr[l][1]), "r"(afr[l][2]), "r"(afr[l][3]), "r"(bb0), "r"(bb1));
                    }
                    z0[2 * ap + h] = make_float2(c0, c2);
                    z1[2 * ap + h] = make_float2(c1, c3);
                }
            }
            fft8<-1>(z0);
            fft8<-1>(z1);
            const int b = 8 * warp + 2 * t;
            float2* d0 = s_f + g * PR + (b % 5) * PB2 + ((13 * b) & 15);
            float2* d1 = s_f + g * PR + ((b + 1) % 5) * PB2 + ((13 * (b + 1)) & 15);
            d0[0] = z0[0]; d1[0] = z1[0];
#pragma unroll
            for (int k1 = 1; k1 < 8; k1++) {
                const float4 tw = *reinterpret_cast<const float4*>(&s_t1[k1 * 80 + b]);
                d0[k1 * PK] = cmul(z0[k1], make_float2(tw.x, tw.y));
                d1[k1 * PK] = cmul(z1[k1], make_float2(tw.z, tw.w));
            }
        }
        CLK(3);
        __syncthreads();
        CLK(4);
#pragma unroll 1
        for (int i = tid; i < 1024; i += NT) {
            float2* base = s_f + (i >> 7) * PR + ((i >> 4) & 7) * PK + (i & 15);
            float2 v0 = base[0], v1 = base[PB2], v2 = base[2 * PB2], v3 = base[3 * PB2], v4 = base[4 * PB2];
            fft5<-1>(v0, v1, v2, v3, v4);
            base[0] = v0; base[PB2] = v1; base[2 * PB2] = v2; base[3 * PB2] = v3; base[4 * PB2] = v4;
        }
        CLK(5);
        __syncthreads();
        CLK(6);
        {
            const int r = tid / 40, u = tid - r * 40;
            const float2* base = s_f + r * PR + (u & 7) * PK + (u >> 3) * PB2;
            float2 v[16];
#pragma unroll
            for (int b1 = 0; b1 < 16; b1++) v[b1] = base[b1];
            fft16<-1>(v);
            if (r > 0) {
                float2* dst = g_buf + ((size_t)r * 128 + s0) * 640 + u;
#pragma unroll
                for (int c1 = 0; c1 < 16; c1++) dst[c1 * 40] = v[c1];
            } else {
                float2* s_z = reinterpret_cast<float2*>(sm);
                const int m0 = 16 * (u >> 3);
#pragma unroll
                for (int c1 = 0; c1 < 16; c1++) {
                    int m = (65 * c1) % 80 + m0;
                    if (m >= 80) m -= 80;
                    s_z[(u & 7) + 8 * m] = v[c1];
                }
            }
        }
        CLK(7);
        __syncthreads();
        CLK(8);
        {
            const float2* s_z = reinterpret_cast<const float2*>(sm);
            const float2 tw8 = s_ta[8 * 16];
            float2* dst = g_buf + (size_t)s0 * 640;
#pragma unroll 1
            for (int k = tid; k <= 320; k += NT) {
                const float2 a = s_z[k], b = s_z[(640 - k) % 640];
                const float2 T0 = make_float2(0.5f * (a.x + b.x), 0.5f * (a.y - b.y));
                float2 T8 = make_float2(0.5f * (a.y + b.y), -0.5f * (a.x - b.x));
                T8 = cmul(T8, tw8);
                if (k < 320) { dst[k] = T0; dst[320 + k] = T8; }
                else { g_ext[s0] = T0; g_ext[128 + s0] = T8; }
            }
        }
    }
    CLK(9);
    TSTAMP(3);
    if (cta < 128) {
        const int r = cta >> 4, b = cta & 15;
        const int q = r ? r : ((b < 8) ? 0 : 8);
        const bool cj = r && b >= 8;
        const int colw = cj ? 601 - 40 * b : 40 * (b & 7);
        const int pp0 = tid / 6, ch = tid - pp0 * 6;
        if (tid < 318) {
#pragma unroll
            for (int it = 0; it < 3; it++) {
                const int pp = pp0 + 53 * it;
                if (pp < 128) {
                    const int ks = q + 16 * pp;
                    const int al = ((((cj ? 2048 - ks : ks) * DF_ + colw) * 2) & ~15) + 16 * ch;
                    if (al + 16 <= S_ * DF_ * 2) {
                        asm volatile("cp.async.cg.shared.global [%0], [%1], 16;" ::"r"(sm_base_u + SM_WF + pp * 96 + ch * 16), "l"((const char*)p.w_r + al) : "memory");
                        asm volatile("cp.async.cg.shared.global [%0], [%1], 16;" ::"r"(sm_base_u + SM_WF + 12288 + pp * 96 + ch * 16), "l"((const char*)p.w_i + al) : "memory");
                    }
                }
            }
        }
        asm volatile("cp.async.commit_group;" ::: "memory");
    }
    grid_arrive(1);
    DBG_STOP(1);
    {
        const int t = lane >> 2;
        const int il = lane & 3;
        float2* colp = g_buf;
        int stride = 640;
        const bool act = cta < 128 || (cta == 128 && warp == 0);
        bool do_store = true;
        float2 wf[16];
        const int r = cta >> 4, b = cta & 15;
        const int q = r ? r : ((b < 8) ? 0 : 8);
        const bool cj = r && b >= 8;
        const int col0 = cj ? 601 - 40 * b : 40 * (b & 7) + (r ? 0 : 0);
        if (cta < 128) {
            const int u = warp * 4 + il;
            if (r) {
                const int kd = 40 * b + u, m = kd >> 3;
                colp = g_buf + (size_t)r * 128 * 640 + (m & 15) * 40 + (m % 5) * 8 + (kd & 7);
            } else {
                colp = g_buf + 40 * b + u;
            }
        } else if (act) { colp = g_ext + (il & 1) * 128; stride = 1; do_store = il < 2; }
        if (cta >= 40 && cta < 120) {
            mbar_wait(bar_w, 0);
            mod_partial(sm + SM_WMOD, s_silu, s_red, tid);
            __syncthreads();
            if (warp == 9) {
                float tt = 0.f;
#pragma unroll
                for (int w = 0; w < 10; w++) tt += s_red[w * 32 + lane];
                g_mod[cta * 32 + lane] = __float2bfloat16_rn(tt);
            }
        }
        if (cta < 128) {
            asm volatile("cp.async.wait_group 0;" ::: "memory");
            __syncthreads();
            const int colw = r ? col0 : 40 * (b & 7);
            const int u = warp * 4 + il;
            const uint32_t mis = (uint32_t)(((cj ? 2048 - q : q) * DF_ + colw) * 2) & 15u;
            const unsigned char* wp = sm + SM_WF + 2 * t * 96 + mis + 2 * (cj ? 39 - u : u);
            const float sg = cj ? -1.0f : 1.0f;
#pragma unroll
            for (int e = 0; e < 2; e++)
#pragma unroll
                for (int k2 = 0; k2 < 8; k2++) {
                    const int o = (e + 16 * k2) * 96;
                    wf[e * 8 + k2] = make_float2(__bfloat162float(*reinterpret_cast<const __nv_bfloat16*>(wp + o)),
                                                 sg * __bfloat162float(*reinterpret_cast<const __nv_bfloat16*>(wp + 12288 + o)));
                }
            if ((b & 7) == 0 && u == 0) {
                const float2* ot = reinterpret_cast<const float2*>(sm + SM_OT) + 2 * t;
#pragma unroll
                for (int i = 0; i < 16; i++) {
                    const float2 o = ot[(i >> 3) + 16 * (i & 7)];
                    wf[i] = make_float2(0.5f * (wf[i].x + o.x), 0.5f * (wf[i].y - sg * o.y));
                }
            }
        } else if (act) {
            const float2* tab = reinterpret_cast<const float2*>(sm + SM_WF) + (il & 1) * 128 + 2 * t;
#pragma unroll
            for (int i = 0; i < 16; i++) wf[i] = tab[(i >> 3) + 16 * (i & 7)];
        }
        TSTAMP(4);
        grid_wait(1, NCTA);
        TSTAMP(5);
        CLK(10);
        prefetch_chunk(p.w1, cta, 1, tid);
        if (cta < 40 && warp == 9) g_modw[cta * 32 + lane] = 0;
        if (act) {
            float4* s_x = reinterpret_cast<float4*>(sm) + warp * (8 * 36);
            float2 v[16];
            float2* sp = colp + t * stride;
            const int st8 = 8 * stride;
#pragma unroll
            for (int n1 = 0; n1 < 16; n1++) v[n1] = ldcg64(sp + n1 * st8);
            CLK(11);
            fft16<-1>(v);
            CLK(12);
#pragma unroll
            for (int m = 0; m < 8; m++) {
                const float4 tw = *reinterpret_cast<const float4*>(&s_t2[t * 16 + 2 * m]);
                const float2 a = m ? cmul(v[2 * m], make_float2(tw.x, tw.y)) : v[0];
                const float2 b = cmul(v[2 * m + 1], make_float2(tw.z, tw.w));
                s_x[m * 36 + lane] = make_float4(a.x, a.y, b.x, b.y);
            }
            __syncwarp();
            float2 a[8], b[8];
#pragma unroll
            for (int n2 = 0; n2 < 8; n2++) {
                const float4 u = s_x[t * 36 + n2 * 4 + il];
                a[n2] = make_float2(u.x, u.y); b[n2] = make_float2(u.z, u.w);
            }
            fft8<-1>(a);
            fft8<-1>(b);
#pragma unroll
            for (int k2 = 0; k2 < 8; k2++) { a[k2] = cmul(a[k2], wf[k2]); b[k2] = cmul(b[k2], wf[8 + k2]); }
            fft8<1>(a);
            fft8<1>(b);
            __syncwarp();
#pragma unroll
            for (int n2 = 0; n2 < 8; n2++) {
                const float4 tw = *reinterpret_cast<const float4*>(&s_t2[n2 * 16 + 2 * t]);
                const float2 ua = n2 ? cmulc(a[n2], make_float2(tw.x, tw.y)) : a[0];
                const float2 ub = n2 ? cmulc(b[n2], make_float2(tw.z, tw.w)) : b[0];
                s_x[t * 36 + n2 * 4 + il] = make_float4(ua.x, ua.y, ub.x, ub.y);
            }
            __syncwarp();
#pragma unroll
            for (int m = 0; m < 8; m++) {
                const float4 u = s_x[m * 36 + lane];
                v[2 * m] = make_float2(u.x, u.y); v[2 * m + 1] = make_float2(u.z, u.w);
            }
            CLK(13);
            fft16<1>(v);
            CLK(14);
            if (do_store) {
#pragma unroll
                for (int n1 = 0; n1 < 16; n1++) sp[n1 * st8] = v[n1];
            }
        }
    }
    CLK(15);
    TSTAMP(6);
    grid_arrive(2);
    DBG_STOP(2);

    {
        grid_wait(2, NCTA);
        TSTAMP(7);
        CLK(16);
        prefetch_chunk(p.w2, cta, 0, tid);
        if (cta == 0 && tid == 0) g_bar[1] = 0;
        if (cta < 128) {
            float2* s_a = reinterpret_cast<float2*>(sm);
            constexpr int A_D1 = 33, A_ROW = 20 * 33 + 2;
            float2* s_b = reinterpret_cast<float2*>(sm + 49152);
            constexpr int B_BETA = 16 * 20 + 4, B_ROW = 2 * B_BETA + 8;
            unsigned char* s_y = sm + 98304;
            float2* s_z = reinterpret_cast<float2*>(sm + 126976);
            if (warp >= 8) {
                const float2 tw8 = s_ta[8 * 16];
                const float2* src = g_buf + (size_t)s0 * 640;
                float2 U0[6], U8[6];
                uint4 mv[4];
#pragma unroll
                for (int i = 0; i < 6; i++) {
                    const int k = tid - 256 + 64 * i;
                    const bool in = k < 320;
                    U0[i] = ldcg64(in ? src + k : g_ext + s0);
                    U8[i] = ldcg64(in ? src + 320 + k : g_ext + 128 + s0);
                }
#pragma unroll
                for (int i = 0; i < 4; i++) if (tid - 256 + 64 * i < 240) mv[i] = ldcg128(g_mod + 2 * 640 + (tid - 256 + 64 * i) * 8);
#pragma unroll
                for (int i = 0; i < 6; i++) {
                    const int k = tid - 256 + 64 * i;
                    const float2 a = U0[i], b = cmulc(U8[i], tw8);
                    if (k <= 320) s_z[k] = make_float2(a.x - b.y, a.y + b.x);
                    if (k > 0 && k < 320) s_z[640 - k] = make_float2(a.x + b.y, b.x - a.y);
                }
                asm volatile("bar.sync 2, 96;" ::: "memory");
#pragma unroll
                for (int i = 0; i < 4; i++) if (tid - 256 + 64 * i < 240) *reinterpret_cast<uint4*>(sm + SM_MODV + (tid - 256 + 64 * i) * 16) = mv[i];
            }
            if (warp < 8) {
                const int r = warp, kb = lane;
                float2 v[20];
                if (r > 0) {
                    const float2* src = g_buf + ((size_t)r * 128 + s0) * 640;
                    const int h = kb >> 3;
                    const float2* bj[5];
#pragma unroll
                    for (int j = 0; j < 5; j++) bj[j] = src + h * 40 + ((j + h) % 5) * 8 + (kb & 7);
#pragma unroll
                    for (int ka = 0; ka < 20; ka++) v[ka] = ldcg64(bj[(4 * ka) % 5] + ((4 * ka) & 15) * 40);
                } else {
                    asm volatile("bar.sync 2, 96;" ::: "memory");
#pragma unroll
                    for (int ka = 0; ka < 20; ka++) v[ka] = s_z[32 * ka + kb];
                }
                CLK(17);
                fft20<1>(v);
                CLK(18);
                float2* d = s_a + r * A_ROW + kb;
                d[0] = v[0];
#pragma unroll
                for (int d1 = 1; d1 < 20; d1++) d[d1 * A_D1] = cmulc(v[d1], s_t3[d1 * 32 + kb]);
            }
            CLK(19);
            __syncthreads();
            CLK(20);
            {
                const int r = tid / 40, u = tid - r * 40, beta = u >= 20, d1 = u - 20 * beta;
                const float2* sp = s_a + r * A_ROW + d1 * A_D1 + beta;
                float2 v[16];
#pragma unroll
                for (int al = 0; al < 16; al++) v[al] = sp[2 * al];
                fft16<1>(v);
                float2* dp = s_b + r * B_ROW + beta * B_BETA + d1;
#pragma unroll
                for (int d2 = 0; d2 < 16; d2++) dp[d2 * 20] = v[d2];
            }
            CLK(21);
            __syncthreads();
            CLK(22);
            {
                const float2 w32 = s_t3[10 * 32 + 2 * (tid / 20)];
                float2 Z[16];
#pragma unroll
                for (int r = 0; r < 8; r++) {
                    const float2 v0 = s_b[r * B_ROW + tid];
                    const float2 v1 = cmulc(s_b[r * B_ROW + B_BETA + tid], w32);
                    float2 A = cadd(v0, v1), B = csub(v0, v1);
                    if (r > 0) {
                        const float2 rho = s_ta[r * 16];
                        A = cmulc(A, rho); B = cmulc(B, rho);
                        Z[r] = make_float2(A.x - B.y, A.y + B.x);
                        Z[16 - r] = make_float2(A.x + B.y, B.x - A.y);
                    } else {
                        Z[0] = make_float2(A.x, B.x);
                        Z[8] = make_float2(A.y, B.y);
                    }
                }
                fft16<1>(Z);
                __nv_bfloat16* yp = reinterpret_cast<__nv_bfloat16*>(s_y) + tid;
#pragma unroll
                for (int j = 0; j < 16; j++) {
                    yp[j * 648] = __float2bfloat16_rn(Z[j].x);
                    yp[j * 648 + 320] = __float2bfloat16_rn(Z[j].y);
                }
            }
            CLK(23);
            uint4 ga[5];
            __syncthreads();
            CLK(24);
            if (warp < 8) {
                const size_t rowoff = (size_t)(128 * lrow + s0) * D_;
                const uint32_t one2 = 0x3f803f80u;
#pragma unroll
                for (int i = 0; i < 5; i++) {
                    ga[i] = *reinterpret_cast<const uint4*>(sm + SM_MODV + (ll + 16 * i) * 16);
                }
#pragma unroll
                for (int i = 0; i < 5; i++) {
                    const uint4 y = *reinterpret_cast<const uint4*>(s_y + lrow * 1296 + (ll + 16 * i) * 16);
                    unpack4(xw + 4 * i, *reinterpret_cast<const uint4*>(sm + SM_X + i * 4096 + lrow * 256 + ll * 16));
                    xw[4 * i + 0] = badd(xw[4 * i + 0], bmul(ga[i].x, y.x));
                    xw[4 * i + 1] = badd(xw[4 * i + 1], bmul(ga[i].y, y.y));
                    xw[4 * i + 2] = badd(xw[4 * i + 2], bmul(ga[i].z, y.z));
                    xw[4 * i + 3] = badd(xw[4 * i + 3], bmul(ga[i].w, y.w));
                    stg128(g_x1 + rowoff + (ll + 16 * i) * 8, xw[4 * i], xw[4 * i + 1], xw[4 * i + 2], xw[4 * i + 3]);
                }
                CLK(25);
#pragma unroll 1
                for (int it = 0; it < 2; it++) {
                    ln_row(xw);
                    if (it == 0) {
#pragma unroll
                        for (int i = 0; i < 5; i++) {
                            const uint4 sb = *reinterpret_cast<const uint4*>(sm + SM_MODV + 1280 + (ll + 16 * i) * 16);
                            const uint4 cb = *reinterpret_cast<const uint4*>(sm + SM_MODV + 2560 + (ll + 16 * i) * 16);
                            xw[4 * i + 0] = badd(bmul(xw[4 * i + 0], badd(one2, cb.x)), sb.x);
                            xw[4 * i + 1] = badd(bmul(xw[4 * i + 1], badd(one2, cb.y)), sb.y);
                            xw[4 * i + 2] = badd(bmul(xw[4 * i + 2], badd(one2, cb.z)), sb.z);
                            xw[4 * i + 3] = badd(bmul(xw[4 * i + 3], badd(one2, cb.w)), sb.w);
                        }
                    }
                }
                CLK(26);
#pragma unroll
                for (int i = 0; i < 5; i++)
                    *reinterpret_cast<uint4*>(sm + lrow * 1296 + (ll + 16 * i) * 16) = make_uint4(xw[4 * i], xw[4 * i + 1], xw[4 * i + 2], xw[4 * i + 3]);
            }
            CLK(27);
            __syncthreads();
            CLK(28);
            {
#pragma unroll
                for (int it = 0; it < 2; it++) {
                    const int dp = (tid >> 1) + 160 * it, h = tid & 1;
                    uint32_t w[8];
#pragma unroll
                    for (int j = 0; j < 8; j++) w[j] = *reinterpret_cast<const uint32_t*>(sm + (8 * h + j) * 1296 + dp * 4);
                    stg128(g_h2 + (size_t)(2 * dp) * H2P + 16 * s0 + 8 * h,
                           __byte_perm(w[0], w[1], 0x5410), __byte_perm(w[2], w[3], 0x5410), __byte_perm(w[4], w[5], 0x5410), __byte_perm(w[6], w[7], 0x5410));
                    stg128(g_h2 + (size_t)(2 * dp + 1) * H2P + 16 * s0 + 8 * h,
                           __byte_perm(w[0], w[1], 0x7632), __byte_perm(w[2], w[3], 0x7632), __byte_perm(w[4], w[5], 0x7632), __byte_perm(w[6], w[7], 0x7632));
                }
            }
        }
    }
    CLK(29);
    TSTAMP(8);
    asm volatile("fence.proxy.async.shared::cta;" ::: "memory");
    grid_arrive(3);
    DBG_STOP(3);

#pragma unroll 1
    for (int g = 0; g < 2; g++) {
        if (tid == 128) {
            asm volatile("prefetch.tensormap [%0];" ::"l"(g ? &tm_w2 : &tm_w1) : "memory");
            asm volatile("prefetch.tensormap [%0];" ::"l"(g ? &tm_u : &tm_h2) : "memory");
        }
        grid_wait(3 + g, NCTA);
        TSTAMP(9 + 2 * g);
        CLK(36 + g);
        if (g == 0) prefetch_chunk(p.w2, cta, 1, tid);
        if (cta == 0 && tid == 0) g_bar[2 + g] = 0;
        if (cta < (g ? 128 : 108)) {
            const int mt = cta >> 2, nt = cta & 3;
            const uint32_t fullb = bars + 128 * g, emptyb = fullb + 64;
            const int NK = g ? 27 : 32;
            float* s_c = reinterpret_cast<float*>(sm);
            uint4 bb = make_uint4(0, 0, 0, 0);
            if (g == 0) bb = ldg128(p.b1 + mt * 64 + (tid & 7) * 8);
            else if (warp >= 5) {
                const int t5 = tid - 160;
#pragma unroll
                for (int it = 0; it < 8; it++) {
                    const int i = t5 + it * 160, row = i / 20, c8 = i - row * 20;
                    *reinterpret_cast<uint4*>(sm + SM_X + i * 16) = ldcg128(g_x1 + (size_t)(mt * 64 + row) * D_ + nt * 160 + c8 * 8);
                }
                if (t5 < 20) *reinterpret_cast<uint4*>(sm + SM_MODV + t5 * 16) = ldcg128(g_mod + 5 * 640 + nt * 160 + t5 * 8);
                else if (t5 < 28) *reinterpret_cast<uint4*>(sm + SM_MODV + 320 + (t5 - 20) * 16) = ldg128(p.b2 + mt * 64 + (t5 - 20) * 8);
            }
            if (warp == 4) {
                const CUtensorMap* ta = g ? &tm_w2 : &tm_w1;
                const CUtensorMap* tb = g ? &tm_u : &tm_h2;
                int s = 0; uint32_t ph = 1;
                asm volatile("fence.proxy.async.global;" ::: "memory");
#pragma unroll 1
                for (int kb = 0; kb < NK; kb++) {
                    mbar_wait(emptyb + 8 * s, ph);
                    if (elect_one()) {
                        const uint32_t sa = sm_base_u + s * G_STAGE_BYTES;
                        mbar_expect(fullb + 8 * s, G_STAGE_BYTES);
                        if (g) tma2d(sa, ta, mt * 64, kb * 64, fullb + 8 * s);
                        else tma3d(sa, ta, mt * 64, 0, kb * 4, fullb + 8 * s);
                        tma2d(sa + 8192, tb, kb * 64, nt * 160, fullb + 8 * s);
                    }
                    if (++s == G_STAGES) { s = 0; ph ^= 1; }
                }
            } else if (warp < 4) {
                float acc[80];
                gemm_consumer(acc, sm_base_u, fullb, NK, tid);
                wg_wait<0>();
                CLK(31 + 2 * g);
                TSTAMP(14 + 2 * g);
                asm volatile("bar.sync 1, 128;" ::: "memory");
                CLK(44 + 4 * g);
                if (g == 0) {
                    float* cp = s_c + (2 * (lane & 3)) * 68 + warp * 16 + (lane >> 2);
#pragma unroll
                    for (int i = 0; i < 20; i++) {
                        cp[(i * 8) * 68] = acc[i * 4]; cp[(i * 8 + 1) * 68] = acc[i * 4 + 1];
                        cp[(i * 8) * 68 + 8] = acc[i * 4 + 2]; cp[(i * 8 + 1) * 68 + 8] = acc[i * 4 + 3];
                    }
                } else {
                    float* cp = s_c + (warp * 16 + (lane >> 2)) * 168 + 2 * (lane & 3);
#pragma unroll
                    for (int i = 0; i < 20; i++) {
                        *reinterpret_cast<float2*>(cp + i * 8) = make_float2(acc[i * 4], acc[i * 4 + 1]);
                        *reinterpret_cast<float2*>(cp + 8 * 168 + i * 8) = make_float2(acc[i * 4 + 2], acc[i * 4 + 3]);
                    }
                }
            }
            {
                CLK(45 + 4 * g); __syncthreads(); CLK(46 + 4 * g);
                if (g == 0) {
#pragma unroll 1
                    for (int d = tid >> 3; d < 160; d += NT / 8) {
                        const float4 a0 = *reinterpret_cast<const float4*>(s_c + d * 68 + (tid & 7) * 8);
                        const float4 a1 = *reinterpret_cast<const float4*>(s_c + d * 68 + (tid & 7) * 8 + 4);
                        uint32_t u[4] = {badd(pack_bf16(a0.x, a0.y), bb.x), badd(pack_bf16(a0.z, a0.w), bb.y),
                                         badd(pack_bf16(a1.x, a1.y), bb.z), badd(pack_bf16(a1.z, a1.w), bb.w)};
#pragma unroll
                        for (int e = 0; e < 4; e++) {
                            const float x0 = bf_lo(u[e]), x1 = bf_hi(u[e]);
                            float e0, e1;
                            asm("ex2.approx.ftz.f32 %0, %1;" : "=f"(e0) : "f"(x0 * fmaf(x0 * x0, -0.1029432397f, -2.3022081985f)));
                            asm("ex2.approx.ftz.f32 %0, %1;" : "=f"(e1) : "f"(x1 * fmaf(x1 * x1, -0.1029432397f, -2.3022081985f)));
                            u[e] = pack_bf16(__fdividef(x0, 1.0f + e0), __fdividef(x1, 1.0f + e1));
                        }
                        stg128(g_u + (size_t)(nt * 160 + d) * F_ + mt * 64 + (tid & 7) * 8, u[0], u[1], u[2], u[3]);
                    }
                } else {
#pragma unroll 1
                    for (int i = tid; i < 64 * 20; i += NT) {
                        const int row = i / 20, c8 = i - row * 20;
                        const uint4 xv = *reinterpret_cast<const uint4*>(sm + SM_X + i * 16);
                        const uint4 gb = *reinterpret_cast<const uint4*>(sm + SM_MODV + c8 * 16);
                        const uint32_t b2 = *reinterpret_cast<const unsigned short*>(sm + SM_MODV + 320 + row * 2);
                        const uint32_t b22 = b2 | (b2 << 16);
                        const float4 a0 = *reinterpret_cast<const float4*>(s_c + row * 168 + c8 * 8);
                        const float4 a1 = *reinterpret_cast<const float4*>(s_c + row * 168 + c8 * 8 + 4);
                        const uint32_t o0 = badd(xv.x, bmul(gb.x, badd(pack_bf16(a0.x, a0.y), b22)));
                        const uint32_t o1 = badd(xv.y, bmul(gb.y, badd(pack_bf16(a0.z, a0.w), b22)));
                        const uint32_t o2 = badd(xv.z, bmul(gb.z, badd(pack_bf16(a1.x, a1.y), b22)));
                        const uint32_t o3 = badd(xv.w, bmul(gb.w, badd(pack_bf16(a1.z, a1.w), b22)));
                        stg128(p.out + (size_t)(mt * 64 + row) * D_ + nt * 160 + c8 * 8, o0, o1, o2, o3);
                    }
                }
            }
        }
        CLK(34 + g);
        TSTAMP(10 + 2 * g);
        if (g == 0) {
            asm volatile("fence.proxy.async.shared::cta;" ::: "memory");
            grid_arrive(4);
            DBG_STOP(4);
        }
    }
}

typedef CUresult (*EncodeFn)(CUtensorMap*, CUtensorMapDataType, cuuint32_t, void*, const cuuint64_t*, const cuuint64_t*,
                             const cuuint32_t*, const cuuint32_t*, CUtensorMapInterleave, CUtensorMapSwizzle,
                             CUtensorMapL2promotion, CUtensorMapFloatOOBfill);

CUtensorMap make_map(EncodeFn enc, void* ptr, int rank, const cuuint64_t* dims, const cuuint64_t* strides_bytes, const cuuint32_t* box,
                     CUtensorMapSwizzle swz = CU_TENSOR_MAP_SWIZZLE_128B) {
    CUtensorMap m;
    cuuint32_t es[3] = {1, 1, 1};
    enc(&m, CU_TENSOR_MAP_DATA_TYPE_BFLOAT16, rank, ptr, dims, strides_bytes, box, es, CU_TENSOR_MAP_INTERLEAVE_NONE,
        swz, CU_TENSOR_MAP_L2_PROMOTION_L2_128B, CU_TENSOR_MAP_FLOAT_OOB_FILL_NONE);
    return m;
}

}

extern "C" void kernel_launch(void* const* d_in, const int* in_sizes, int n_in, void* d_out, int out_size) {
    (void)in_sizes; (void)n_in; (void)out_size;
    static EncodeFn enc = nullptr;
    static void *p_h2 = nullptr, *p_u = nullptr;
    if (!enc) {
        void* fn = nullptr;
        cudaDriverEntryPointQueryResult qr;
        cudaGetDriverEntryPoint("cuTensorMapEncodeTiled", &fn, cudaEnableDefault, &qr);
        enc = (EncodeFn)fn;
        cudaGetSymbolAddress(&p_h2, g_h2);
        cudaGetSymbolAddress(&p_u, g_u);
        cudaFuncSetAttribute(fused_kernel, cudaFuncAttributeMaxDynamicSharedMemorySize, SM_TOTAL + 1024);
    }
    Params p;
    p.x = (const __nv_bfloat16*)d_in[0];
    p.w_r = (const __nv_bfloat16*)d_in[1];
    p.w_i = (const __nv_bfloat16*)d_in[2];
    p.w1 = (const __nv_bfloat16*)d_in[4];
    p.b1 = (const __nv_bfloat16*)d_in[5];
    p.w2 = (const __nv_bfloat16*)d_in[6];
    p.b2 = (const __nv_bfloat16*)d_in[7];
    p.c = (const __nv_bfloat16*)d_in[8];
    p.w_mod = (const __nv_bfloat16*)d_in[9];
    p.out = (__nv_bfloat16*)d_out;
    p.stop_after = 0;

    CUtensorMap tm_h2, tm_w1, tm_w2, tm_u, tm_wm, tm_x;
    {
        cuuint64_t dims[2] = {2048, 640}, str[1] = {H2P * 2};
        cuuint32_t box[2] = {64, 160};
        tm_h2 = make_map(enc, p_h2, 2, dims, str, box);
    }
    {
        cuuint64_t dims[3] = {1728, 16, 128}, str[2] = {(cuuint64_t)128 * 1728 * 2, 1728 * 2};
        cuuint32_t box[3] = {64, 16, 4};
        tm_w1 = make_map(enc, (void*)p.w1, 3, dims, str, box);
    }
    {
        cuuint64_t dims[2] = {2048, 1728}, str[1] = {2048 * 2};
        cuuint32_t box[2] = {64, 64};
        tm_w2 = make_map(enc, (void*)p.w2, 2, dims, str, box);
    }
    {
        cuuint64_t dims[2] = {1728, 640}, str[1] = {1728 * 2};
        cuuint32_t box[2] = {64, 160};
        tm_u = make_map(enc, p_u, 2, dims, str, box);
    }
    {
        cuuint64_t dims[2] = {3840, 640}, str[1] = {3840 * 2};
        cuuint32_t box[2] = {32, 128};
        tm_wm = make_map(enc, (void*)p.w_mod, 2, dims, str, box, CU_TENSOR_MAP_SWIZZLE_NONE);
    }
    {
        cuuint64_t dims[3] = {640, 16, 128}, str[2] = {(cuuint64_t)128 * 640 * 2, 640 * 2};
        cuuint32_t box[3] = {128, 16, 1};
        tm_x = make_map(enc, (void*)p.x, 3, dims, str, box, CU_TENSOR_MAP_SWIZZLE_NONE);
    }
    fused_kernel<<<NCTA, NT, SM_TOTAL + 1024, cudaStreamPerThread>>>(tm_h2, tm_w1, tm_w2, tm_u, tm_wm, tm_x, p);
}
```

```cpp
#include <cuda_runtime.h>
#include <cuda_bf16.h>
#include <cuda.h>
#include <stdint.h>

namespace {

constexpr int S_ = 2048, D_ = 640, F_ = 1728, DF_ = 321;
constexpr int NT = 320;
constexpr int NCTA = 132;

__device__ float2 g_buf[8 * 128 * 640];
__device__ float2 g_ext[2 * 128];
__device__ __align__(16) __nv_bfloat16 g_mod[6 * 640];
__device__ __align__(1024) __nv_bfloat16 g_x1[S_ * D_];
constexpr int H2P = S_ + 64;
__device__ __align__(1024) __nv_bfloat16 g_h2[D_ * H2P];
__device__ __align__(1024) __nv_bfloat16 g_u[D_ * F_];
__device__ unsigned int g_bar[8];
__device__ __align__(16) unsigned int g_modw[1280];
#define DBG_STOP(n)
#define TSTAMP(i)
#define TSTAMPT(i, T)
#define CLK(i)

__device__ __forceinline__ uint32_t smem_u32(const void* p) { return (uint32_t)__cvta_generic_to_shared(p); }
__device__ __forceinline__ float bf16r(float x) { return __bfloat162float(__float2bfloat16_rn(x)); }
__device__ __forceinline__ float bf_lo(uint32_t v) { return __uint_as_float(v << 16); }
__device__ __forceinline__ float bf_hi(uint32_t v) { return __uint_as_float(v & 0xffff0000u); }
__device__ __forceinline__ uint32_t pack_bf16(float lo, float hi) {
    uint32_t r;
    asm("cvt.rn.bf16x2.f32 %0, %1, %2;" : "=r"(r) : "f"(hi), "f"(lo));
    return r;
}
__device__ __forceinline__ float2 cmul(float2 a, float2 b) {
    return make_float2(fmaf(a.x, b.x, -a.y * b.y), fmaf(a.x, b.y, a.y * b.x));
}
__device__ __forceinline__ float2 cmulc(float2 a, float2 b) {
    return make_float2(fmaf(a.x, b.x, a.y * b.y), fmaf(a.y, b.x, -a.x * b.y));
}
__device__ __forceinline__ float2 cadd(float2 a, float2 b) { return make_float2(a.x + b.x, a.y + b.y); }
__device__ __forceinline__ float2 csub(float2 a, float2 b) { return make_float2(a.x - b.x, a.y - b.y); }

template <int DIR>
__device__ __forceinline__ float2 mul_i(float2 a) {
    return DIR > 0 ? make_float2(-a.y, a.x) : make_float2(a.y, -a.x);
}
template <int DIR>
__device__ __forceinline__ void fft4(float2& a0, float2& a1, float2& a2, float2& a3) {
    float2 t0 = cadd(a0, a2), t1 = csub(a0, a2), t2 = cadd(a1, a3), t3 = mul_i<DIR>(csub(a1, a3));
    a0 = cadd(t0, t2); a2 = csub(t0, t2); a1 = cadd(t1, t3); a3 = csub(t1, t3);
}
template <int DIR>
__device__ __forceinline__ float2 mul_w8_1(float2 a) {
    const float c = 0.70710678118654752440f;
    return DIR > 0 ? make_float2((a.x - a.y) * c, (a.x + a.y) * c) : make_float2((a.x + a.y) * c, (a.y - a.x) * c);
}
template <int DIR>
__device__ __forceinline__ float2 mul_w8_3(float2 a) {
    const float c = 0.70710678118654752440f;
    return DIR > 0 ? make_float2(-(a.x + a.y) * c, (a.x - a.y) * c) : make_float2((a.y - a.x) * c, -(a.x + a.y) * c);
}
template <int DIR>
__device__ __forceinline__ float2 mul_cs(float2 a, float c, float s) {
    return DIR > 0 ? make_float2(fmaf(a.x, c, -a.y * s), fmaf(a.y, c, a.x * s))
                   : make_float2(fmaf(a.x, c, a.y * s), fmaf(a.y, c, -a.x * s));
}
template <int DIR>
__device__ __forceinline__ void fft8(float2 (&v)[8]) {
    fft4<DIR>(v[0], v[2], v[4], v[6]);
    fft4<DIR>(v[1], v[3], v[5], v[7]);
    float2 o1 = mul_w8_1<DIR>(v[3]), o2 = mul_i<DIR>(v[5]), o3 = mul_w8_3<DIR>(v[7]), o0 = v[1];
    float2 e0 = v[0], e1 = v[2], e2 = v[4], e3 = v[6];
    v[0] = cadd(e0, o0); v[4] = csub(e0, o0);
    v[1] = cadd(e1, o1); v[5] = csub(e1, o1);
    v[2] = cadd(e2, o2); v[6] = csub(e2, o2);
    v[3] = cadd(e3, o3); v[7] = csub(e3, o3);
}
template <int DIR>
__device__ __forceinline__ void fft16(float2 (&v)[16]) {
    const float c1 = 0.92387953251128675613f, s1 = 0.38268343236508977173f;
#pragma unroll
    for (int n2 = 0; n2 < 4; n2++) fft4<DIR>(v[n2], v[4 + n2], v[8 + n2], v[12 + n2]);
    v[5] = mul_cs<DIR>(v[5], c1, s1);
    v[6] = mul_w8_1<DIR>(v[6]);
    v[7] = mul_cs<DIR>(v[7], s1, c1);
    v[9] = mul_w8_1<DIR>(v[9]);
    v[10] = mul_i<DIR>(v[10]);
    v[11] = mul_w8_3<DIR>(v[11]);
    v[13] = mul_cs<DIR>(v[13], s1, c1);
    v[14] = mul_w8_3<DIR>(v[14]);
    v[15] = mul_cs<DIR>(v[15], -c1, -s1);
#pragma unroll
    for (int k1 = 0; k1 < 4; k1++) fft4<DIR>(v[4 * k1], v[4 * k1 + 1], v[4 * k1 + 2], v[4 * k1 + 3]);
    float2 t;
#define SWP(a, b) t = v[a]; v[a] = v[b]; v[b] = t;
    SWP(1, 4) SWP(2, 8) SWP(3, 12) SWP(6, 9) SWP(7, 13) SWP(11, 14)
#undef SWP
}
template <int DIR>
__device__ __forceinline__ void fft5(float2& x0, float2& x1, float2& x2, float2& x3, float2& x4) {
    const float c1 = 0.30901699437494742410f, c2 = -0.80901699437494742410f;
    const float s1 = 0.95105651629515357212f, s2 = 0.58778525229247312917f;
    float2 t1 = cadd(x1, x4), t2 = cadd(x2, x3), t3 = csub(x1, x4), t4 = csub(x2, x3);
    float2 a1 = make_float2(fmaf(c2, t2.x, fmaf(c1, t1.x, x0.x)), fmaf(c2, t2.y, fmaf(c1, t1.y, x0.y)));
    float2 a2 = make_float2(fmaf(c1, t2.x, fmaf(c2, t1.x, x0.x)), fmaf(c1, t2.y, fmaf(c2, t1.y, x0.y)));
    float2 b1 = make_float2(fmaf(s2, t4.x, s1 * t3.x), fmaf(s2, t4.y, s1 * t3.y));
    float2 b2 = make_float2(fmaf(-s1, t4.x, s2 * t3.x), fmaf(-s1, t4.y, s2 * t3.y));
    x0 = make_float2(x0.x + t1.x + t2.x, x0.y + t1.y + t2.y);
    float2 ib1 = mul_i<DIR>(b1), ib2 = mul_i<DIR>(b2);
    x1 = cadd(a1, ib1); x4 = csub(a1, ib1);
    x2 = cadd(a2, ib2); x3 = csub(a2, ib2);
}
template <int DIR>
__device__ __forceinline__ void fft20(float2 (&v)[20]) {
    float2 t[4][5];
#pragma unroll
    for (int n1 = 0; n1 < 4; n1++)
#pragma unroll
        for (int n2 = 0; n2 < 5; n2++) t[n1][n2] = v[(5 * n1 + 4 * n2) % 20];
#pragma unroll
    for (int n1 = 0; n1 < 4; n1++) fft5<DIR>(t[n1][0], t[n1][1], t[n1][2], t[n1][3], t[n1][4]);
#pragma unroll
    for (int k2 = 0; k2 < 5; k2++) fft4<DIR>(t[0][k2], t[1][k2], t[2][k2], t[3][k2]);
#pragma unroll
    for (int k1 = 0; k1 < 4; k1++)
#pragma unroll
        for (int k2 = 0; k2 < 5; k2++) v[(5 * k1 + 16 * k2) % 20] = t[k1][k2];
}

__device__ __forceinline__ void mbar_init(uint32_t a, uint32_t c) { asm volatile("mbarrier.init.shared::cta.b64 [%0], %1;" ::"r"(a), "r"(c)); }
__device__ __forceinline__ void mbar_expect(uint32_t a, uint32_t b) {
    asm volatile("mbarrier.arrive.expect_tx.shared::cta.b64 _, [%0], %1;" ::"r"(a), "r"(b) : "memory");
}
__device__ __forceinline__ void mbar_arrive(uint32_t a) { asm volatile("mbarrier.arrive.shared::cta.b64 _, [%0];" ::"r"(a) : "memory"); }
__device__ __forceinline__ uint32_t mbar_try(uint32_t a, uint32_t ph) {
    uint32_t ok;
    asm volatile("{\n.reg .pred p;\nmbarrier.try_wait.parity.shared::cta.b64 p, [%1], %2;\nselp.u32 %0, 1, 0, p;\n}"
                 : "=r"(ok) : "r"(a), "r"(ph) : "memory");
    return ok;
}
__device__ __forceinline__ void mbar_wait(uint32_t a, uint32_t ph) {
    if (mbar_try(a, ph)) return;
    int it = 0;
    while (!mbar_try(a, ph)) { if (++it > 4000000) __trap(); }
}
__device__ __forceinline__ uint32_t elect_one() {
    uint32_t pred;
    asm volatile("{\n.reg .pred p;\nelect.sync _|p, 0xffffffff;\nselp.u32 %0, 1, 0, p;\n}" : "=r"(pred));
    return pred;
}
__device__ __forceinline__ void tma2d(uint32_t dst, const CUtensorMap* m, int c0, int c1, uint32_t bar) {
    asm volatile("cp.async.bulk.tensor.2d.shared::cluster.global.mbarrier::complete_tx::bytes [%0], [%1, {%3, %4}], [%2];"
                 ::"r"(dst), "l"(m), "r"(bar), "r"(c0), "r"(c1) : "memory");
}
__device__ __forceinline__ void tma3d(uint32_t dst, const CUtensorMap* m, int c0, int c1, int c2, uint32_t bar) {
    asm volatile("cp.async.bulk.tensor.3d.shared::cluster.global.mbarrier::complete_tx::bytes [%0], [%1, {%3, %4, %5}], [%2];"
                 ::"r"(dst), "l"(m), "r"(bar), "r"(c0), "r"(c1), "r"(c2) : "memory");
}
__device__ __forceinline__ uint64_t make_desc(uint32_t addr, uint32_t lbo, uint32_t sbo) {
    uint64_t d = 0;
    d |= (uint64_t)((addr & 0x3FFFF) >> 4);
    d |= (uint64_t)((lbo >> 4) & 0x3FFF) << 16;
    d |= (uint64_t)((sbo >> 4) & 0x3FFF) << 32;
    d |= (uint64_t)1 << 62;
    return d;
}
#define WG_FENCE() asm volatile("wgmma.fence.sync.aligned;" ::: "memory")
#define WG_COMMIT() asm volatile("wgmma.commit_group.sync.aligned;" ::: "memory")
template <int N>
__device__ __forceinline__ void wg_wait() { asm volatile("wgmma.wait_group.sync.aligned %0;" ::"n"(N) : "memory"); }

__device__ __forceinline__ void wgmma_tn_160(float (&d)[80], uint64_t da, uint64_t db, int scale_d) {
    asm volatile("{\n.reg .pred p;\nsetp.ne.b32 p, %82, 0;\n"
        "wgmma.mma_async.sync.aligned.m64n160k16.f32.bf16.bf16 {%0, %1, %2, %3, %4, %5, %6, %7, %8, %9, %10, %11, %12, %13, %14, %15, %16, %17, %18, %19, %20, %21, %22, %23, %24, %25, %26, %27, %28, %29, %30, %31, %32, %33, %34, %35, %36, %37, %38, %39, %40, %41, %42, %43, %44, %45, %46, %47, %48, %49, %50, %51, %52, %53, %54, %55, %56, %57, %58, %59, %60, %61, %62, %63, %64, %65, %66, %67, %68, %69, %70, %71, %72, %73, %74, %75, %76, %77, %78, %79}, %80, %81, p, 1, 1, 1, 0;\n}\n"
        : "+f"(d[0]), "+f"(d[1]), "+f"(d[2]), "+f"(d[3]), "+f"(d[4]), "+f"(d[5]), "+f"(d[6]), "+f"(d[7]), "+f"(d[8]), "+f"(d[9]), "+f"(d[10]), "+f"(d[11]), "+f"(d[12]), "+f"(d[13]), "+f"(d[14]), "+f"(d[15]), "+f"(d[16]), "+f"(d[17]), "+f"(d[18]), "+f"(d[19]), "+f"(d[20]), "+f"(d[21]), "+f"(d[22]), "+f"(d[23]), "+f"(d[24]), "+f"(d[25]), "+f"(d[26]), "+f"(d[27]), "+f"(d[28]), "+f"(d[29]), "+f"(d[30]), "+f"(d[31]), "+f"(d[32]), "+f"(d[33]), "+f"(d[34]), "+f"(d[35]), "+f"(d[36]), "+f"(d[37]), "+f"(d[38]), "+f"(d[39]), "+f"(d[40]), "+f"(d[41]), "+f"(d[42]), "+f"(d[43]), "+f"(d[44]), "+f"(d[45]), "+f"(d[46]), "+f"(d[47]), "+f"(d[48]), "+f"(d[49]), "+f"(d[50]), "+f"(d[51]), "+f"(d[52]), "+f"(d[53]), "+f"(d[54]), "+f"(d[55]), "+f"(d[56]), "+f"(d[57]), "+f"(d[58]), "+f"(d[59]), "+f"(d[60]), "+f"(d[61]), "+f"(d[62]), "+f"(d[63]), "+f"(d[64]), "+f"(d[65]), "+f"(d[66]), "+f"(d[67]), "+f"(d[68]), "+f"(d[69]), "+f"(d[70]), "+f"(d[71]), "+f"(d[72]), "+f"(d[73]), "+f"(d[74]), "+f"(d[75]), "+f"(d[76]), "+f"(d[77]), "+f"(d[78]), "+f"(d[79])
        : "l"(da), "l"(db), "r"(scale_d));
}

__device__ __forceinline__ void red_release(unsigned int* p) {
    asm volatile("red.release.gpu.global.add.u32 [%0], 1;" ::"l"(p) : "memory");
}
__device__ __forceinline__ unsigned int ld_acquire(const unsigned int* p) {
    unsigned int v;
    asm volatile("ld.acquire.gpu.global.u32 %0, [%1];" : "=r"(v) : "l"(p) : "memory");
    return v;
}
__device__ __forceinline__ void spin_until(const unsigned int* p, unsigned int target) {
    int it = 0;
    while (ld_acquire(p) < target) { if (++it > 20000000) __trap(); }
}
__device__ __forceinline__ void grid_arrive(int k) {
    __syncthreads();
    if (threadIdx.x == 0) red_release(&g_bar[k]);
}
__device__ __forceinline__ void grid_wait(int k, unsigned int target) {
    if (threadIdx.x == 0) spin_until(&g_bar[k], target);
    __syncthreads();
}

constexpr int SM_STAGE_BYTES = 172032;
constexpr int SM_WF = 90112;
constexpr int SM_OT = 114688;
constexpr int SM_WMOD = 131072;
constexpr int G_STAGES = 7, G_STAGE_BYTES = 8192 + 20480;
constexpr int SM_T1 = SM_STAGE_BYTES;
constexpr int SM_T3 = SM_T1 + 5120;
constexpr int SM_T2 = SM_T3 + 5120;
constexpr int SM_TA = SM_T2 + 1024;
constexpr int SM_RED = SM_TA + 1152;
constexpr int SM_SILU = SM_RED + 1280;
constexpr int SM_BARS = 200704;
constexpr int SM_MODV = SM_BARS + 512;
constexpr int SM_X = SM_MODV + 3840;
constexpr int SM_TOTAL = SM_X + 20480;

struct Params {
    const __nv_bfloat16* x;
    const __nv_bfloat16* w_r;
    const __nv_bfloat16* w_i;
    const __nv_bfloat16* w1;
    const __nv_bfloat16* b1;
    const __nv_bfloat16* w2;
    const __nv_bfloat16* b2;
    const __nv_bfloat16* c;
    const __nv_bfloat16* w_mod;
    __nv_bfloat16* out;
    int stop_after;
};

__device__ __forceinline__ uint32_t badd(uint32_t a, uint32_t b) { uint32_t r; asm("add.rn.bf16x2 %0, %1, %2;" : "=r"(r) : "r"(a), "r"(b)); return r; }
__device__ __forceinline__ uint32_t bsub(uint32_t a, uint32_t b) { uint32_t r; asm("sub.rn.bf16x2 %0, %1, %2;" : "=r"(r) : "r"(a), "r"(b)); return r; }
__device__ __forceinline__ uint32_t bmul(uint32_t a, uint32_t b) { uint32_t r; asm("mul.rn.bf16x2 %0, %1, %2;" : "=r"(r) : "r"(a), "r"(b)); return r; }
__device__ __forceinline__ uint4 ldg128(const void* p) { return __ldg(reinterpret_cast<const uint4*>(p)); }
__device__ __forceinline__ uint4 ldcg128(const void* p) {
    uint4 v;
    asm volatile("ld.global.cg.v4.u32 {%0,%1,%2,%3}, [%4];" : "=r"(v.x), "=r"(v.y), "=r"(v.z), "=r"(v.w) : "l"(p));
    return v;
}
__device__ __forceinline__ void stg128(void* p, uint32_t a, uint32_t b, uint32_t c, uint32_t d) {
    asm volatile("st.global.v4.u32 [%0], {%1,%2,%3,%4};" ::"l"(p), "r"(a), "r"(b), "r"(c), "r"(d) : "memory");
}
__device__ __forceinline__ float2 ldcg64(const float2* p) {
    float2 v;
    asm volatile("ld.global.cg.v2.f32 {%0,%1}, [%2];" : "=f"(v.x), "=f"(v.y) : "l"(p));
    return v;
}

__device__ __forceinline__ void ln_row(uint32_t (&w)[20]) {
    float sa[4] = {0.f, 0.f, 0.f, 0.f};
#pragma unroll
    for (int i = 0; i < 20; i += 2) { sa[0] += bf_lo(w[i]); sa[1] += bf_hi(w[i]); sa[2] += bf_lo(w[i + 1]); sa[3] += bf_hi(w[i + 1]); }
    float s = (sa[0] + sa[1]) + (sa[2] + sa[3]);
#pragma unroll
    for (int m = 8; m >= 1; m >>= 1) s += __shfl_xor_sync(0xffffffffu, s, m);
    const float mu = s * (1.0f / 640.0f);
    float qa[4] = {0.f, 0.f, 0.f, 0.f};
#pragma unroll
    for (int i = 0; i < 20; i += 2) {
        const float d0 = bf_lo(w[i]) - mu, d1 = bf_hi(w[i]) - mu, d2 = bf_lo(w[i + 1]) - mu, d3 = bf_hi(w[i + 1]) - mu;
        qa[0] = fmaf(d0, d0, qa[0]); qa[1] = fmaf(d1, d1, qa[1]); qa[2] = fmaf(d2, d2, qa[2]); qa[3] = fmaf(d3, d3, qa[3]);
    }
    float q = (qa[0] + qa[1]) + (qa[2] + qa[3]);
#pragma unroll
    for (int m = 8; m >= 1; m >>= 1) q += __shfl_xor_sync(0xffffffffu, q, m);
    const float var = bf16r(q * (1.0f / 640.0f));
    const float den = bf16r(sqrtf(bf16r(var + 1e-5f)));
    const float r = __fdiv_rn(1.0f, den);
    const uint32_t m2 = pack_bf16(mu, mu);
#pragma unroll
    for (int i = 0; i < 20; i++) {
        const uint32_t d = bsub(w[i], m2);
        w[i] = pack_bf16(bf_lo(d) * r, bf_hi(d) * r);
    }
}
__device__ __forceinline__ void unpack4(uint32_t* w, uint4 v) { w[0] = v.x; w[1] = v.y; w[2] = v.z; w[3] = v.w; }

__device__ __forceinline__ void gemm_consumer(float (&acc)[80], uint32_t sm_base_u, uint32_t fullb, int NK, int tid) {
    const uint32_t emptyb = fullb + 64;
    const uint64_t da0 = make_desc(sm_base_u, 8192, 1024);
    const uint64_t db0 = make_desc(sm_base_u + 8192, 16, 1024);
    uint32_t ph = 0;
    mbar_wait(fullb, 0);
#pragma unroll 1
    for (int kb0 = 0; kb0 < NK; kb0 += G_STAGES) {
#pragma unroll
        for (int s = 0; s < G_STAGES; s++) {
            const int kb = kb0 + s;
            if (kb < NK) {
                constexpr uint64_t one = 1;
                const uint64_t so = one * ((s * G_STAGE_BYTES) >> 4);
                WG_FENCE();
#pragma unroll
                for (int k = 0; k < 4; k++) wgmma_tn_160(acc, da0 + so + k * 128, db0 + so + k * 2, (kb > 0 || k > 0) ? 1 : 0);
                WG_COMMIT();
                const int sn = (s + 1) % G_STAGES;
                if (kb + 1 < NK) mbar_wait(fullb + 8 * sn, (s + 1 == G_STAGES) ? ph ^ 1 : ph);
                wg_wait<1>();
                if (kb > 0 && tid == 0) mbar_arrive(emptyb + 8 * ((s + G_STAGES - 1) % G_STAGES));
            }
        }
        ph ^= 1;
    }
}

__device__ __forceinline__ void load_wmod_slab(const CUtensorMap* tm, uint32_t dst, int cta, uint32_t bar) {
    mbar_expect(bar, 640 * 64);
#pragma unroll
    for (int i = 0; i < 5; i++) tma2d(dst + i * 128 * 64, tm, cta * 32, i * 128, bar);
}
__device__ __forceinline__ void mod_partial(const unsigned char* slab, const float* s_silu, float* s_red, int tid) {
    uint4 wm[8];
#pragma unroll
    for (int i = 0; i < 8; i++) wm[i] = *reinterpret_cast<const uint4*>(slab + ((tid >> 2) + 80 * i) * 64 + (tid & 3) * 16);
    float acc[8];
#pragma unroll
    for (int e = 0; e < 8; e++) acc[e] = 0.f;
#pragma unroll
    for (int i = 0; i < 8; i++) {
        const float sv = s_silu[(tid >> 2) + 80 * i];
        acc[0] = fmaf(sv, bf_lo(wm[i].x), acc[0]); acc[1] = fmaf(sv, bf_hi(wm[i].x), acc[1]);
        acc[2] = fmaf(sv, bf_lo(wm[i].y), acc[2]); acc[3] = fmaf(sv, bf_hi(wm[i].y), acc[3]);
        acc[4] = fmaf(sv, bf_lo(wm[i].z), acc[4]); acc[5] = fmaf(sv, bf_hi(wm[i].z), acc[5]);
        acc[6] = fmaf(sv, bf_lo(wm[i].w), acc[6]); acc[7] = fmaf(sv, bf_hi(wm[i].w), acc[7]);
    }
    const int lane = tid & 31;
    const bool u16 = lane & 16, u8 = lane & 8, u4 = lane & 4;
    float b4[4], b2[2], b1;
#pragma unroll
    for (int e = 0; e < 4; e++) {
        const float keep = u16 ? acc[e + 4] : acc[e], send = u16 ? acc[e] : acc[e + 4];
        b4[e] = keep + __shfl_xor_sync(0xffffffffu, send, 16);
    }
#pragma unroll
    for (int e = 0; e < 2; e++) {
        const float keep = u8 ? b4[e + 2] : b4[e], send = u8 ? b4[e] : b4[e + 2];
        b2[e] = keep + __shfl_xor_sync(0xffffffffu, send, 8);
    }
    {
        const float keep = u4 ? b2[1] : b2[0], send = u4 ? b2[0] : b2[1];
        b1 = keep + __shfl_xor_sync(0xffffffffu, send, 4);
    }
    s_red[(tid >> 5) * 32 + (lane & 3) * 8 + (u16 ? 4 : 0) + (u8 ? 2 : 0) + (u4 ? 1 : 0)] = b1;
}

__device__ __forceinline__ void prefetch_chunk(const void* base, int cta, int half, int tid) {
    if (tid == 288 && cta < 128)
        asm volatile("cp.async.bulk.prefetch.L2.global [%0], %1;" ::"l"((const char*)base + (cta * 2 + half) * 27648), "r"(27648));
}

__global__ void __launch_bounds__(NT, 1)
fused_kernel(const __grid_constant__ CUtensorMap tm_h2, const __grid_constant__ CUtensorMap tm_w1,
             const __grid_constant__ CUtensorMap tm_w2, const __grid_constant__ CUtensorMap tm_u,
             const __grid_constant__ CUtensorMap tm_wm, const __grid_constant__ CUtensorMap tm_x, const Params p) {
    extern __shared__ unsigned char sm_raw[];
    const uint32_t sm_base_u = __shfl_sync(0xffffffffu, (smem_u32(sm_raw) + 1023u) & ~1023u, 0);
    unsigned char* sm = sm_raw + (sm_base_u - smem_u32(sm_raw));
    float2* s_t1 = reinterpret_cast<float2*>(sm + SM_T1);
    float2* s_t3 = reinterpret_cast<float2*>(sm + SM_T3);
    float2* s_t2 = reinterpret_cast<float2*>(sm + SM_T2);
    float2* s_ta = reinterpret_cast<float2*>(sm + SM_TA);
    float* s_red = reinterpret_cast<float*>(sm + SM_RED);
    const uint32_t bars = sm_base_u + SM_BARS;

    const int tid = threadIdx.x, lane = tid & 31;
    const int warp = __shfl_sync(0xffffffffu, tid >> 5, 0);
    const int cta = blockIdx.x;
    const int s0 = cta;
    const int lrow = 2 * warp + (lane >> 4);
    const int ll = lane & 15;
    TSTAMP(0);

    float* s_silu = reinterpret_cast<float*>(sm + SM_SILU);
    const uint32_t bar_x = bars + 256, bar_w = bars + 264;
    if (tid == 288) {
        for (int i = 0; i < 8; i++) { mbar_init(bars + 8 * i, 1); mbar_init(bars + 64 + 8 * i, 1); mbar_init(bars + 128 + 8 * i, 1); mbar_init(bars + 192 + 8 * i, 1); }
        mbar_init(bar_x, 1); mbar_init(bar_w, 1);
        asm volatile("fence.mbarrier_init.release.cluster;" ::: "memory");
        if (cta < 40) load_wmod_slab(&tm_wm, sm_base_u + SM_WMOD, cta, bar_w);
        if (cta == 0) g_bar[4] = 0;
        __nanosleep(400);
        if (cta < 128) {
            mbar_expect(bar_x, 16 * 1280);
#pragma unroll
            for (int i = 0; i < 5; i++) tma3d(sm_base_u + SM_X + i * 4096, &tm_x, i * 128, 0, s0, bar_x);
        }
    }
    uint4 cvv = make_uint4(0, 0, 0, 0);
    if (tid >= 208 && tid < 288) cvv = ldg128(p.c + (tid - 208) * 8);
    uint32_t xw[20];
    TSTAMP(17);
#pragma unroll 1
    for (int i = tid; i < 1552 && tid < 288; i += 288) {
        float ang;
        if (i < 640) ang = (float)((i % 80) * (i / 80)) * (1.0f / 320.0f);
        else if (i < 1280) ang = (float)(((i - 640) & 31) * ((i - 640) >> 5)) * (1.0f / 320.0f);
        else if (i < 1408) ang = (float)(((i - 1280) & 15) * ((i - 1280) >> 4)) * (1.0f / 64.0f);
        else ang = (float)(((128 * ((i - 1408) & 15) + s0) * ((i - 1408) >> 4)) & 2047) * (1.0f / 1024.0f);
        float s, c;
        sincospif(-ang, &s, &c);
        s_t1[i] = make_float2(c, s);
    }
    if (tid >= 208 && tid < 288) {
        const uint32_t w4[4] = {cvv.x, cvv.y, cvv.z, cvv.w};
        float o[8];
#pragma unroll
        for (int e = 0; e < 4; e++) {
            const float c0 = bf_lo(w4[e]), c1 = bf_hi(w4[e]);
            o[2 * e] = bf16r(__fdividef(c0, 1.0f + exp2f(-1.4426950409f * c0)));
            o[2 * e + 1] = bf16r(__fdividef(c1, 1.0f + exp2f(-1.4426950409f * c1)));
        }
        *reinterpret_cast<float4*>(s_silu + (tid - 208) * 8) = make_float4(o[0], o[1], o[2], o[3]);
        *reinterpret_cast<float4*>(s_silu + (tid - 208) * 8 + 4) = make_float4(o[4], o[5], o[6], o[7]);
    }
    TSTAMP(18);
    __syncthreads();
    if (cta < 40 && warp >= 8) {
        mbar_wait(bar_w, 0);
        const int t6 = tid - 256, rg = t6 >> 2, cg = t6 & 3;
        float acc[8];
#pragma unroll
        for (int e = 0; e < 8; e++) acc[e] = 0.f;
#pragma unroll 8
        for (int i = 0; i < 40; i++) {
            const uint4 w = *reinterpret_cast<const uint4*>(sm + SM_WMOD + (rg + 16 * i) * 64 + cg * 16);
            const float sv = s_silu[rg + 16 * i];
            acc[0] = fmaf(sv, bf_lo(w.x), acc[0]); acc[1] = fmaf(sv, bf_hi(w.x), acc[1]);
            acc[2] = fmaf(sv, bf_lo(w.y), acc[2]); acc[3] = fmaf(sv, bf_hi(w.y), acc[3]);
            acc[4] = fmaf(sv, bf_lo(w.z), acc[4]); acc[5] = fmaf(sv, bf_hi(w.z), acc[5]);
            acc[6] = fmaf(sv, bf_lo(w.w), acc[6]); acc[7] = fmaf(sv, bf_hi(w.w), acc[7]);
        }
        const bool u16 = lane & 16, u8 = lane & 8, u4 = lane & 4;
        float b4[4], b2[2], b1;
#pragma unroll
        for (int e = 0; e < 4; e++) {
            const float keep = u16 ? acc[e + 4] : acc[e], send = u16 ? acc[e] : acc[e + 4];
            b4[e] = keep + __shfl_xor_sync(0xffffffffu, send, 16);
        }
#pragma unroll
        for (int e = 0; e < 2; e++) {
            const float keep = u8 ? b4[e + 2] : b4[e], send = u8 ? b4[e] : b4[e + 2];
            b2[e] = keep + __shfl_xor_sync(0xffffffffu, send, 8);
        }
        {
            const float keep = u4 ? b2[1] : b2[0], send = u4 ? b2[0] : b2[1];
            b1 = keep + __shfl_xor_sync(0xffffffffu, send, 4);
        }
        s_red[(warp - 8) * 32 + (lane & 3) * 8 + (u16 ? 4 : 0) + (u8 ? 2 : 0) + (u4 ? 1 : 0)] = b1;
        asm volatile("bar.sync 3, 64;" ::: "memory");
        if (warp == 9) {
            const float t = s_red[lane] + s_red[32 + lane];
            asm volatile("st.relaxed.gpu.global.u32 [%0], %1;" ::"l"(&g_modw[cta * 32 + lane]), "r"(0x80000000u | (pack_bf16(t, 0.f) & 0xffffu)) : "memory");
            TSTAMPT(23, 288);
        }
    }
    if (tid == 288) {
        const uint32_t cW = 9968;
        const uint32_t off = cta * cW, n = min(cW, 1314816u - min(off, 1314816u));
        if (n) {
            asm volatile("cp.async.bulk.prefetch.L2.global [%0], %1;" ::"l"((const char*)p.w_r + off), "r"(n));
            asm volatile("cp.async.bulk.prefetch.L2.global [%0], %1;" ::"l"((const char*)p.w_i + off), "r"(n));
        }
        if (cta >= 40 && cta < 120) load_wmod_slab(&tm_wm, sm_base_u + SM_WMOD, cta, bar_w);
        asm volatile("prefetch.tensormap [%0];" ::"l"(&tm_h2) : "memory");
        asm volatile("prefetch.tensormap [%0];" ::"l"(&tm_w1) : "memory");
        asm volatile("prefetch.tensormap [%0];" ::"l"(&tm_w2) : "memory");
        asm volatile("prefetch.tensormap [%0];" ::"l"(&tm_u) : "memory");
    }

    if (cta == 128 && tid < 256) {
        const int q = 8 * (tid >> 7), ks = q + 16 * (tid & 127), ksm = (2048 - ks) & 2047;
        reinterpret_cast<float2*>(sm + SM_WF)[tid] =
            make_float2(0.5f * (__bfloat162float(__ldg(p.w_r + ks * DF_ + 320)) + __bfloat162float(__ldg(p.w_r + ksm * DF_ + 320))),
                        0.5f * (__bfloat162float(__ldg(p.w_i + ks * DF_ + 320)) - __bfloat162float(__ldg(p.w_i + ksm * DF_ + 320))));
    }

    if (cta < 128) {
        uint32_t afr[3][4];
        {
            const int g = lane >> 2, t = lane & 3;
            const float scale = 1.0f / (2048.0f * 640.0f);
            float cr[4], ci[4];
#pragma unroll
            for (int i = 0; i < 4; i++) {
                const int j = 2 * t + (i & 1) + (i >> 1) * 8;
                const float2 w = s_ta[g * 16 + j];
                cr[i] = w.x * scale;
                ci[i] = (g == 0 ? ((i & 1) ? -1.0f : 1.0f) : w.y) * scale;
            }
#pragma unroll
            for (int l = 0; l < 3; l++) {
                afr[l][0] = pack_bf16(cr[0], cr[1]);
                afr[l][1] = pack_bf16(ci[0], ci[1]);
                afr[l][2] = pack_bf16(cr[2], cr[3]);
                afr[l][3] = pack_bf16(ci[2], ci[3]);
                cr[0] -= bf_lo(afr[l][0]); cr[1] -= bf_hi(afr[l][0]); ci[0] -= bf_lo(afr[l][1]); ci[1] -= bf_hi(afr[l][1]);
                cr[2] -= bf_lo(afr[l][2]); cr[3] -= bf_hi(afr[l][2]); ci[2] -= bf_lo(afr[l][3]); ci[3] -= bf_hi(afr[l][3]);
            }
        }
        if (warp < 8) {
            mbar_wait(bar_x, 0);
#pragma unroll
            for (int i = 0; i < 5; i++) unpack4(xw + 4 * i, *reinterpret_cast<const uint4*>(sm + SM_X + i * 4096 + lrow * 256 + ll * 16));
            ln_row(xw);
            TSTAMP(1);
        } else {
            {
                const int t6 = tid - 256;
                uint4 a[3], b[3];
                int it = 0;
                unsigned ok;
                do {
                    ok = 0x80000000u;
#pragma unroll
                    for (int i = 0; i < 3; i++) {
                        const int c = min(t6 + 64 * i, 159);
                        asm volatile("ld.relaxed.gpu.global.v4.u32 {%0,%1,%2,%3}, [%4];" : "=r"(a[i].x), "=r"(a[i].y), "=r"(a[i].z), "=r"(a[i].w) : "l"(g_modw + c * 8) : "memory");
                        asm volatile("ld.relaxed.gpu.global.v4.u32 {%0,%1,%2,%3}, [%4];" : "=r"(b[i].x), "=r"(b[i].y), "=r"(b[i].z), "=r"(b[i].w) : "l"(g_modw + c * 8 + 4) : "memory");
                    }
#pragma unroll
                    for (int i = 0; i < 3; i++) ok &= a[i].x & a[i].y & a[i].z & a[i].w & b[i].x & b[i].y & b[i].z & b[i].w;
                    if (++it > 20000000) __trap();
                } while ((ok >> 31) == 0);
#pragma unroll
                for (int i = 0; i < 3; i++) {
                    const int c = t6 + 64 * i;
                    if (c < 160)
                        *reinterpret_cast<uint4*>(sm + SM_MODV + c * 16) =
                            make_uint4(__byte_perm(a[i].x, a[i].y, 0x5410), __byte_perm(a[i].z, a[i].w, 0x5410), __byte_perm(b[i].x, b[i].y, 0x5410), __byte_perm(b[i].z, b[i].w, 0x5410));
                }
            }
            prefetch_chunk(p.w1, cta, 0, tid);
            if ((cta & 7) == 0) {
                const int r = cta >> 4, b = cta & 15;
                const int q = r ? r : ((b < 8) ? 0 : 8);
                const bool cj = r && b >= 8;
                const int kc = cj ? 320 : 0;
#pragma unroll
                for (int i = 0; i < 2; i++) {
                    const int pp = tid - 256 + 64 * i, ks = q + 16 * pp;
                    const int orow = cj ? ks : ((2048 - ks) & 2047);
                    reinterpret_cast<float2*>(sm + SM_OT)[pp] =
                        make_float2(__bfloat162float(__ldg(p.w_r + orow * DF_ + kc)), __bfloat162float(__ldg(p.w_i + orow * DF_ + kc)));
                }
            }
        }
        __syncthreads();
        TSTAMP(2);
        CLK(0);

        if (warp < 8) {
            uint4 sa[5], ca[5];
#pragma unroll
            for (int i = 0; i < 5; i++) {
                sa[i] = *reinterpret_cast<const uint4*>(sm + SM_MODV + (ll + 16 * i) * 16);
                ca[i] = *reinterpret_cast<const uint4*>(sm + SM_MODV + 1280 + (ll + 16 * i) * 16);
            }
            const uint32_t one2 = 0x3f803f80u;
#pragma unroll
            for (int i = 0; i < 5; i++) {
                uint4 h;
                h.x = badd(bmul(xw[4 * i + 0], badd(one2, ca[i].x)), sa[i].x);
                h.y = badd(bmul(xw[4 * i + 1], badd(one2, ca[i].y)), sa[i].y);
                h.z = badd(bmul(xw[4 * i + 2], badd(one2, ca[i].z)), sa[i].z);
                h.w = badd(bmul(xw[4 * i + 3], badd(one2, ca[i].w)), sa[i].w);
                *reinterpret_cast<uint4*>(sm + lrow * 1296 + (ll + 16 * i) * 16) = h;
            }
        }
        CLK(1);
        __syncthreads();
        CLK(2);
        float2* s_f = reinterpret_cast<float2*>(sm + 24576);
        constexpr int PB2 = 24, PK = 121, PR = 968;
        {
            const int g = lane >> 2, t = lane & 3;
            float2 z0[8], z1[8];
            const uint32_t laddr = sm_base_u + (((lane >> 3) & 1) * 8 + (lane & 7)) * 1296 + (80 * (lane >> 4) + 8 * warp) * 2;
#pragma unroll
            for (int ap = 0; ap < 4; ap++) {
                uint32_t b0, b1, b2, b3;
                asm volatile("ldmatrix.sync.aligned.m8n8.x4.trans.shared.b16 {%0,%1,%2,%3}, [%4];"
                             : "=r"(b0), "=r"(b1), "=r"(b2), "=r"(b3) : "r"(laddr + ap * 320));
#pragma unroll
                for (int h = 0; h < 2; h++) {
                    float c0 = 0.f, c1 = 0.f, c2 = 0.f, c3 = 0.f;
                    const uint32_t bb0 = h ? b2 : b0, bb1 = h ? b3 : b1;
#pragma unroll
                    for (int l = 2; l >= 0; l--) {
                        asm volatile("mma.sync.aligned.m16n8k16.row.col.f32.bf16.bf16.f32 {%0,%1,%2,%3}, {%4,%5,%6,%7}, {%8,%9}, {%0,%1,%2,%3};"
                                     : "+f"(c0), "+f"(c1), "+f"(c2), "+f"(c3)
                                     : "r"(afr[l][0]), "r"(afr[l][1]), "r"(afr[l][2]), "r"(afr[l][3]), "r"(bb0), "r"(bb1));
                    }
                    z0[2 * ap + h] = make_float2(c0, c2);
                    z1[2 * ap + h] = make_float2(c1, c3);
                }
            }
            fft8<-1>(z0);
            fft8<-1>(z1);
            const int b = 8 * warp + 2 * t;
            float2* d0 = s_f + g * PR + (b % 5) * PB2 + ((13 * b) & 15);
            float2* d1 = s_f + g * PR + ((b + 1) % 5) * PB2 + ((13 * (b + 1)) & 15);
            d0[0] = z0[0]; d1[0] = z1[0];
#pragma unroll
            for (int k1 = 1; k1 < 8; k1++) {
                const float4 tw = *reinterpret_cast<const float4*>(&s_t1[k1 * 80 + b]);
                d0[k1 * PK] = cmul(z0[k1], make_float2(tw.x, tw.y));
                d1[k1 * PK] = cmul(z1[k1], make_float2(tw.z, tw.w));
            }
        }
        CLK(3);
        __syncthreads();
        CLK(4);
#pragma unroll 1
        for (int i = tid; i < 1024; i += NT) {
            float2* base = s_f + (i >> 7) * PR + ((i >> 4) & 7) * PK + (i & 15);
            float2 v0 = base[0], v1 = base[PB2], v2 = base[2 * PB2], v3 = base[3 * PB2], v4 = base[4 * PB2];
            fft5<-1>(v0, v1, v2, v3, v4);
            base[0] = v0; base[PB2] = v1; base[2 * PB2] = v2; base[3 * PB2] = v3; base[4 * PB2] = v4;
        }
        CLK(5);
        __syncthreads();
        CLK(6);
        {
            const int r = tid / 40, u = tid - r * 40;
            const float2* base = s_f + r * PR + (u & 7) * PK + (u >> 3) * PB2;
            float2 v[16];
#pragma unroll
            for (int b1 = 0; b1 < 16; b1++) v[b1] = base[b1];
            fft16<-1>(v);
            if (r > 0) {
                float2* dst = g_buf + ((size_t)r * 128 + s0) * 640 + u;
#pragma unroll
                for (int c1 = 0; c1 < 16; c1++) dst[c1 * 40] = v[c1];
            } else {
                float2* s_z = reinterpret_cast<float2*>(sm);
                const int m0 = 16 * (u >> 3);
#pragma unroll
                for (int c1 = 0; c1 < 16; c1++) {
                    int m = (65 * c1) % 80 + m0;
                    if (m >= 80) m -= 80;
                    s_z[(u & 7) + 8 * m] = v[c1];
                }
            }
        }
        CLK(7);
        __syncthreads();
        CLK(8);
        {
            const float2* s_z = reinterpret_cast<const float2*>(sm);
            const float2 tw8 = s_ta[8 * 16];
            float2* dst = g_buf + (size_t)s0 * 640;
#pragma unroll 1
            for (int k = tid; k <= 320; k += NT) {
                const float2 a = s_z[k], b = s_z[(640 - k) % 640];
                const float2 T0 = make_float2(0.5f * (a.x + b.x), 0.5f * (a.y - b.y));
                float2 T8 = make_float2(0.5f * (a.y + b.y), -0.5f * (a.x - b.x));
                T8 = cmul(T8, tw8);
                if (k < 320) { dst[k] = T0; dst[320 + k] = T8; }
                else { g_ext[s0] = T0; g_ext[128 + s0] = T8; }
            }
        }
    }
    CLK(9);
    TSTAMP(3);
    if (cta < 128) {
        const int r = cta >> 4, b = cta & 15;
        const int q = r ? r : ((b < 8) ? 0 : 8);
        const bool cj = r && b >= 8;
        const int colw = cj ? 601 - 40 * b : 40 * (b & 7);
        const int pp0 = tid / 6, ch = tid - pp0 * 6;
        if (tid < 318) {
#pragma unroll
            for (int it = 0; it < 3; it++) {
                const int pp = pp0 + 53 * it;
                if (pp < 128) {
                    const int ks = q + 16 * pp;
                    const int al = ((((cj ? 2048 - ks : ks) * DF_ + colw) * 2) & ~15) + 16 * ch;
                    if (al + 16 <= S_ * DF_ * 2) {
                        asm volatile("cp.async.cg.shared.global [%0], [%1], 16;" ::"r"(sm_base_u + SM_WF + pp * 96 + ch * 16), "l"((const char*)p.w_r + al) : "memory");
                        asm volatile("cp.async.cg.shared.global [%0], [%1], 16;" ::"r"(sm_base_u + SM_WF + 12288 + pp * 96 + ch * 16), "l"((const char*)p.w_i + al) : "memory");
                    }
                }
            }
        }
        asm volatile("cp.async.commit_group;" ::: "memory");
    }
    grid_arrive(1);
    DBG_STOP(1);
    {
        const int t = lane >> 2;
        const int il = lane & 3;
        float2* colp = g_buf;
        int stride = 640;
        const bool act = cta < 128 || (cta == 128 && warp == 0);
        bool do_store = true;
        float2 wf[16];
        const int r = cta >> 4, b = cta & 15;
        const int q = r ? r : ((b < 8) ? 0 : 8);
        const bool cj = r && b >= 8;
        const int col0 = cj ? 601 - 40 * b : 40 * (b & 7) + (r ? 0 : 0);
        if (cta < 128) {
            const int u = warp * 4 + il;
            if (r) {
                const int kd = 40 * b + u, m = kd >> 3;
                colp = g_buf + (size_t)r * 128 * 640 + (m & 15) * 40 + (m % 5) * 8 + (kd & 7);
            } else {
                colp = g_buf + 40 * b + u;
            }
        } else if (act) { colp = g_ext + (il & 1) * 128; stride = 1; do_store = il < 2; }
        if (cta >= 40 && cta < 120) {
            mbar_wait(bar_w, 0);
            mod_partial(sm + SM_WMOD, s_silu, s_red, tid);
            __syncthreads();
            if (warp == 9) {
                float tt = 0.f;
#pragma unroll
                for (int w = 0; w < 10; w++) tt += s_red[w * 32 + lane];
                g_mod[cta * 32 + lane] = __float2bfloat16_rn(tt);
            }
        }
        if (cta < 128) {
            asm volatile("cp.async.wait_group 0;" ::: "memory");
            __syncthreads();
            const int colw = r ? col0 : 40 * (b & 7);
            const int u = warp * 4 + il;
            const uint32_t mis = (uint32_t)(((cj ? 2048 - q : q) * DF_ + colw) * 2) & 15u;
            const unsigned char* wp = sm + SM_WF + 2 * t * 96 + mis + 2 * (cj ? 39 - u : u);
            const float sg = cj ? -1.0f : 1.0f;
#pragma unroll
            for (int e = 0; e < 2; e++)
#pragma unroll
                for (int k2 = 0; k2 < 8; k2++) {
                    const int o = (e + 16 * k2) * 96;
                    wf[e * 8 + k2] = make_float2(__bfloat162float(*reinterpret_cast<const __nv_bfloat16*>(wp + o)),
                                                 sg * __bfloat162float(*reinterpret_cast<const __nv_bfloat16*>(wp + 12288 + o)));
                }
            if ((b & 7) == 0 && u == 0) {
                const float2* ot = reinterpret_cast<const float2*>(sm + SM_OT) + 2 * t;
#pragma unroll
                for (int i = 0; i < 16; i++) {
                    const float2 o = ot[(i >> 3) + 16 * (i & 7)];
                    wf[i] = make_float2(0.5f * (wf[i].x + o.x), 0.5f * (wf[i].y - sg * o.y));
                }
            }
        } else if (act) {
            const float2* tab = reinterpret_cast<const float2*>(sm + SM_WF) + (il & 1) * 128 + 2 * t;
#pragma unroll
            for (int i = 0; i < 16; i++) wf[i] = tab[(i >> 3) + 16 * (i & 7)];
        }
        TSTAMP(4);
        grid_wait(1, NCTA);
        TSTAMP(5);
        CLK(10);
        prefetch_chunk(p.w1, cta, 1, tid);
        if (cta < 40 && warp == 9) g_modw[cta * 32 + lane] = 0;
        if (act) {
            float4* s_x = reinterpret_cast<float4*>(sm) + warp * (8 * 36);
            float2 v[16];
            float2* sp = colp + t * stride;
            const int st8 = 8 * stride;
#pragma unroll
            for (int n1 = 0; n1 < 16; n1++) v[n1] = ldcg64(sp + n1 * st8);
            CLK(11);
            fft16<-1>(v);
            CLK(12);
#pragma unroll
            for (int m = 0; m < 8; m++) {
                const float4 tw = *reinterpret_cast<const float4*>(&s_t2[t * 16 + 2 * m]);
                const float2 a = m ? cmul(v[2 * m], make_float2(tw.x, tw.y)) : v[0];
                const float2 b = cmul(v[2 * m + 1], make_float2(tw.z, tw.w));
                s_x[m * 36 + lane] = make_float4(a.x, a.y, b.x, b.y);
            }
            __syncwarp();
            float2 a[8], b[8];
#pragma unroll
            for (int n2 = 0; n2 < 8; n2++) {
                const float4 u = s_x[t * 36 + n2 * 4 + il];
                a[n2] = make_float2(u.x, u.y); b[n2] = make_float2(u.z, u.w);
            }
            fft8<-1>(a);
            fft8<-1>(b);
#pragma unroll
            for (int k2 = 0; k2 < 8; k2++) { a[k2] = cmul(a[k2], wf[k2]); b[k2] = cmul(b[k2], wf[8 + k2]); }
            fft8<1>(a);
            fft8<1>(b);
            __syncwarp();
#pragma unroll
            for (int n2 = 0; n2 < 8; n2++) {
                const float4 tw = *reinterpret_cast<const float4*>(&s_t2[n2 * 16 + 2 * t]);
                const float2 ua = n2 ? cmulc(a[n2], make_float2(tw.x, tw.y)) : a[0];
                const float2 ub = n2 ? cmulc(b[n2], make_float2(tw.z, tw.w)) : b[0];
                s_x[t * 36 + n2 * 4 + il] = make_float4(ua.x, ua.y, ub.x, ub.y);
            }
            __syncwarp();
#pragma unroll
            for (int m = 0; m < 8; m++) {
                const float4 u = s_x[m * 36 + lane];
                v[2 * m] = make_float2(u.x, u.y); v[2 * m + 1] = make_float2(u.z, u.w);
            }
            CLK(13);
            fft16<1>(v);
            CLK(14);
            if (do_store) {
#pragma unroll
                for (int n1 = 0; n1 < 16; n1++) sp[n1 * st8] = v[n1];
            }
        }
    }
    CLK(15);
    TSTAMP(6);
    grid_arrive(2);
    DBG_STOP(2);

    {
        grid_wait(2, NCTA);
        TSTAMP(7);
        CLK(16);
        prefetch_chunk(p.w2, cta, 0, tid);
        if (cta == 0 && tid == 0) g_bar[1] = 0;
        if (cta < 128) {
            float2* s_a = reinterpret_cast<float2*>(sm);
            constexpr int A_D1 = 33, A_ROW = 20 * 33 + 2;
            float2* s_b = reinterpret_cast<float2*>(sm + 49152);
            constexpr int B_BETA = 16 * 20 + 4, B_ROW = 2 * B_BETA + 8;
            unsigned char* s_y = sm + 98304;
            float2* s_z = reinterpret_cast<float2*>(sm + 126976);
            if (warp >= 8) {
                const float2 tw8 = s_ta[8 * 16];
                const float2* src = g_buf + (size_t)s0 * 640;
                float2 U0[6], U8[6];
                uint4 mv[4];
#pragma unroll
                for (int i = 0; i < 6; i++) {
                    const int k = tid - 256 + 64 * i;
                    const bool in = k < 320;
                    U0[i] = ldcg64(in ? src + k : g_ext + s0);
                    U8[i] = ldcg64(in ? src + 320 + k : g_ext + 128 + s0);
                }
#pragma unroll
                for (int i = 0; i < 4; i++) if (tid - 256 + 64 * i < 240) mv[i] = ldcg128(g_mod + 2 * 640 + (tid - 256 + 64 * i) * 8);
#pragma unroll
                for (int i = 0; i < 6; i++) {
                    const int k = tid - 256 + 64 * i;
                    const float2 a = U0[i], b = cmulc(U8[i], tw8);
                    if (k <= 320) s_z[k] = make_float2(a.x - b.y, a.y + b.x);
                    if (k > 0 && k < 320) s_z[640 - k] = make_float2(a.x + b.y, b.x - a.y);
                }
                asm volatile("bar.sync 2, 96;" ::: "memory");
#pragma unroll
                for (int i = 0; i < 4; i++) if (tid - 256 + 64 * i < 240) *reinterpret_cast<uint4*>(sm + SM_MODV + (tid - 256 + 64 * i) * 16) = mv[i];
            }
            if (warp < 8) {
                const int r = warp, kb = lane;
                float2 v[20];
                if (r > 0) {
                    const float2* src = g_buf + ((size_t)r * 128 + s0) * 640;
                    const int h = kb >> 3;
                    const float2* bj[5];
#pragma unroll
                    for (int j = 0; j < 5; j++) bj[j] = src + h * 40 + ((j + h) % 5) * 8 + (kb & 7);
#pragma unroll
                    for (int ka = 0; ka < 20; ka++) v[ka] = ldcg64(bj[(4 * ka) % 5] + ((4 * ka) & 15) * 40);
                } else {
                    asm volatile("bar.sync 2, 96;" ::: "memory");
#pragma unroll
                    for (int ka = 0; ka < 20; ka++) v[ka] = s_z[32 * ka + kb];
                }
                CLK(17);
                fft20<1>(v);
                CLK(18);
                float2* d = s_a + r * A_ROW + kb;
                d[0] = v[0];
#pragma unroll
                for (int d1 = 1; d1 < 20; d1++) d[d1 * A_D1] = cmulc(v[d1], s_t3[d1 * 32 + kb]);
            }
            CLK(19);
            __syncthreads();
            CLK(20);
            {
                const int r = tid / 40, u = tid - r * 40, beta = u >= 20, d1 = u - 20 * beta;
                const float2* sp = s_a + r * A_ROW + d1 * A_D1 + beta;
                float2 v[16];
#pragma unroll
                for (int al = 0; al < 16; al++) v[al] = sp[2 * al];
                fft16<1>(v);
                float2* dp = s_b + r * B_ROW + beta * B_BETA + d1;
#pragma unroll
                for (int d2 = 0; d2 < 16; d2++) dp[d2 * 20] = v[d2];
            }
            CLK(21);
            __syncthreads();
            CLK(22);
            {
                const float2 w32 = s_t3[10 * 32 + 2 * (tid / 20)];
                float2 Z[16];
#pragma unroll
                for (int r = 0; r < 8; r++) {
                    const float2 v0 = s_b[r * B_ROW + tid];
                    const float2 v1 = cmulc(s_b[r * B_ROW + B_BETA + tid], w32);
                    float2 A = cadd(v0, v1), B = csub(v0, v1);
                    if (r > 0) {
                        const float2 rho = s_ta[r * 16];
                        A = cmulc(A, rho); B = cmulc(B, rho);
                        Z[r] = make_float2(A.x - B.y, A.y + B.x);
                        Z[16 - r] = make_float2(A.x + B.y, B.x - A.y);
                    } else {
                        Z[0] = make_float2(A.x, B.x);
                        Z[8] = make_float2(A.y, B.y);
                    }
                }
                fft16<1>(Z);
                __nv_bfloat16* yp = reinterpret_cast<__nv_bfloat16*>(s_y) + tid;
#pragma unroll
                for (int j = 0; j < 16; j++) {
                    yp[j * 648] = __float2bfloat16_rn(Z[j].x);
                    yp[j * 648 + 320] = __float2bfloat16_rn(Z[j].y);
                }
            }
            CLK(23);
            uint4 ga[5];
            __syncthreads();
            CLK(24);
            if (warp < 8) {
                const size_t rowoff = (size_t)(128 * lrow + s0) * D_;
                const uint32_t one2 = 0x3f803f80u;
#pragma unroll
                for (int i = 0; i < 5; i++) {
                    ga[i] = *reinterpret_cast<const uint4*>(sm + SM_MODV + (ll + 16 * i) * 16);
                }
#pragma unroll
                for (int i = 0; i < 5; i++) {
                    const uint4 y = *reinterpret_cast<const uint4*>(s_y + lrow * 1296 + (ll + 16 * i) * 16);
                    unpack4(xw + 4 * i, *reinterpret_cast<const uint4*>(sm + SM_X + i * 4096 + lrow * 256 + ll * 16));
                    xw[4 * i + 0] = badd(xw[4 * i + 0], bmul(ga[i].x, y.x));
                    xw[4 * i + 1] = badd(xw[4 * i + 1], bmul(ga[i].y, y.y));
                    xw[4 * i + 2] = badd(xw[4 * i + 2], bmul(ga[i].z, y.z));
                    xw[4 * i + 3] = badd(xw[4 * i + 3], bmul(ga[i].w, y.w));
                    stg128(g_x1 + rowoff + (ll + 16 * i) * 8, xw[4 * i], xw[4 * i + 1], xw[4 * i + 2], xw[4 * i + 3]);
                }
                CLK(25);
#pragma unroll 1
                for (int it = 0; it < 2; it++) {
                    ln_row(xw);
                    if (it == 0) {
#pragma unroll
                        for (int i = 0; i < 5; i++) {
                            const uint4 sb = *reinterpret_cast<const uint4*>(sm + SM_MODV + 1280 + (ll + 16 * i) * 16);
                            const uint4 cb = *reinterpret_cast<const uint4*>(sm + SM_MODV + 2560 + (ll + 16 * i) * 16);
                            xw[4 * i + 0] = badd(bmul(xw[4 * i + 0], badd(one2, cb.x)), sb.x);
                            xw[4 * i + 1] = badd(bmul(xw[4 * i + 1], badd(one2, cb.y)), sb.y);
                            xw[4 * i + 2] = badd(bmul(xw[4 * i + 2], badd(one2, cb.z)), sb.z);
                            xw[4 * i + 3] = badd(bmul(xw[4 * i + 3], badd(one2, cb.w)), sb.w);
                        }
                    }
                }
                CLK(26);
#pragma unroll
                for (int i = 0; i < 5; i++)
                    *reinterpret_cast<uint4*>(sm + lrow * 1296 + (ll + 16 * i) * 16) = make_uint4(xw[4 * i], xw[4 * i + 1], xw[4 * i + 2], xw[4 * i + 3]);
            }
            CLK(27);
            __syncthreads();
            CLK(28);
            {
#pragma unroll
                for (int it = 0; it < 2; it++) {
                    const int dp = (tid >> 1) + 160 * it, h = tid & 1;
                    uint32_t w[8];
#pragma unroll
                    for (int j = 0; j < 8; j++) w[j] = *reinterpret_cast<const uint32_t*>(sm + (8 * h + j) * 1296 + dp * 4);
                    stg128(g_h2 + (size_t)(2 * dp) * H2P + 16 * s0 + 8 * h,
                           __byte_perm(w[0], w[1], 0x5410), __byte_perm(w[2], w[3], 0x5410), __byte_perm(w[4], w[5], 0x5410), __byte_perm(w[6], w[7], 0x5410));
                    stg128(g_h2 + (size_t)(2 * dp + 1) * H2P + 16 * s0 + 8 * h,
                           __byte_perm(w[0], w[1], 0x7632), __byte_perm(w[2], w[3], 0x7632), __byte_perm(w[4], w[5], 0x7632), __byte_perm(w[6], w[7], 0x7632));
                }
            }
        }
    }
    CLK(29);
    TSTAMP(8);
    asm volatile("fence.proxy.async.shared::cta;" ::: "memory");
    grid_arrive(3);
    DBG_STOP(3);

#pragma unroll 1
    for (int g = 0; g < 2; g++) {
        if (tid == 128) {
            asm volatile("prefetch.tensormap [%0];" ::"l"(g ? &tm_w2 : &tm_w1) : "memory");
            asm volatile("prefetch.tensormap [%0];" ::"l"(g ? &tm_u : &tm_h2) : "memory");
        }
        grid_wait(3 + g, NCTA);
        TSTAMP(9 + 2 * g);
        CLK(36 + g);
        if (g == 0) prefetch_chunk(p.w2, cta, 1, tid);
        if (cta == 0 && tid == 0) g_bar[2 + g] = 0;
        if (cta < (g ? 128 : 108)) {
            const int mt = cta >> 2, nt = cta & 3;
            const uint32_t fullb = bars + 128 * g, emptyb = fullb + 64;
            const int NK = g ? 27 : 32;
            float* s_c = reinterpret_cast<float*>(sm);
            uint4 bb = make_uint4(0, 0, 0, 0);
            if (g == 0) bb = ldg128(p.b1 + mt * 64 + (tid & 7) * 8);
            else if (warp >= 5) {
                const int t5 = tid - 160;
#pragma unroll
                for (int it = 0; it < 8; it++) {
                    const int i = t5 + it * 160, row = i / 20, c8 = i - row * 20;
                    *reinterpret_cast<uint4*>(sm + SM_X + i * 16) = ldcg128(g_x1 + (size_t)(mt * 64 + row) * D_ + nt * 160 + c8 * 8);
                }
                if (t5 < 20) *reinterpret_cast<uint4*>(sm + SM_MODV + t5 * 16) = ldcg128(g_mod + 5 * 640 + nt * 160 + t5 * 8);
                else if (t5 < 28) *reinterpret_cast<uint4*>(sm + SM_MODV + 320 + (t5 - 20) * 16) = ldg128(p.b2 + mt * 64 + (t5 - 20) * 8);
            }
            if (warp == 4) {
                const CUtensorMap* ta = g ? &tm_w2 : &tm_w1;
                const CUtensorMap* tb = g ? &tm_u : &tm_h2;
                int s = 0; uint32_t ph = 1;
                asm volatile("fence.proxy.async.global;" ::: "memory");
#pragma unroll 1
                for (int kb = 0; kb < NK; kb++) {
                    mbar_wait(emptyb + 8 * s, ph);
                    if (elect_one()) {
                        const uint32_t sa = sm_base_u + s * G_STAGE_BYTES;
                        mbar_expect(fullb + 8 * s, G_STAGE_BYTES);
                        if (g) tma2d(sa, ta, mt * 64, kb * 64, fullb + 8 * s);
                        else tma3d(sa, ta, mt * 64, 0, kb * 4, fullb + 8 * s);
                        tma2d(sa + 8192, tb, kb * 64, nt * 160, fullb + 8 * s);
                    }
                    if (++s == G_STAGES) { s = 0; ph ^= 1; }
                }
            } else if (warp < 4) {
                float acc[80];
                gemm_consumer(acc, sm_base_u, fullb, NK, tid);
                wg_wait<0>();
                CLK(31 + 2 * g);
                TSTAMP(14 + 2 * g);
                asm volatile("bar.sync 1, 128;" ::: "memory");
                CLK(44 + 4 * g);
                if (g == 0) {
                    float* cp = s_c + (2 * (lane & 3)) * 68 + warp * 16 + (lane >> 2);
#pragma unroll
                    for (int i = 0; i < 20; i++) {
                        cp[(i * 8) * 68] = acc[i * 4]; cp[(i * 8 + 1) * 68] = acc[i * 4 + 1];
                        cp[(i * 8) * 68 + 8] = acc[i * 4 + 2]; cp[(i * 8 + 1) * 68 + 8] = acc[i * 4 + 3];
                    }
                } else {
                    float* cp = s_c + (warp * 16 + (lane >> 2)) * 168 + 2 * (lane & 3);
#pragma unroll
                    for (int i = 0; i < 20; i++) {
                        *reinterpret_cast<float2*>(cp + i * 8) = make_float2(acc[i * 4], acc[i * 4 + 1]);
                        *reinterpret_cast<float2*>(cp + 8 * 168 + i * 8) = make_float2(acc[i * 4 + 2], acc[i * 4 + 3]);
                    }
                }
            }
            {
                CLK(45 + 4 * g); __syncthreads(); CLK(46 + 4 * g);
                if (g == 0) {
#pragma unroll 1
                    for (int d = tid >> 3; d < 160; d += NT / 8) {
                        const float4 a0 = *reinterpret_cast<const float4*>(s_c + d * 68 + (tid & 7) * 8);
                        const float4 a1 = *reinterpret_cast<const float4*>(s_c + d * 68 + (tid & 7) * 8 + 4);
                        uint32_t u[4] = {badd(pack_bf16(a0.x, a0.y), bb.x), badd(pack_bf16(a0.z, a0.w), bb.y),
                                         badd(pack_bf16(a1.x, a1.y), bb.z), badd(pack_bf16(a1.z, a1.w), bb.w)};
#pragma unroll
                        for (int e = 0; e < 4; e++) {
                            const float x0 = bf_lo(u[e]), x1 = bf_hi(u[e]);
                            float e0, e1;
                            asm("ex2.approx.ftz.f32 %0, %1;" : "=f"(e0) : "f"(x0 * fmaf(x0 * x0, -0.1029432397f, -2.3022081985f)));
                            asm("ex2.approx.ftz.f32 %0, %1;" : "=f"(e1) : "f"(x1 * fmaf(x1 * x1, -0.1029432397f, -2.3022081985f)));
                            u[e] = pack_bf16(__fdividef(x0, 1.0f + e0), __fdividef(x1, 1.0f + e1));
                        }
                        stg128(g_u + (size_t)(nt * 160 + d) * F_ + mt * 64 + (tid & 7) * 8, u[0], u[1], u[2], u[3]);
                    }
                } else {
#pragma unroll 1
                    for (int i = tid; i < 64 * 20; i += NT) {
                        const int row = i / 20, c8 = i - row * 20;
                        const uint4 xv = *reinterpret_cast<const uint4*>(sm + SM_X + i * 16);
                        const uint4 gb = *reinterpret_cast<const uint4*>(sm + SM_MODV + c8 * 16);
                        const uint32_t b2 = *reinterpret_cast<const unsigned short*>(sm + SM_MODV + 320 + row * 2);
                        const uint32_t b22 = b2 | (b2 << 16);
                        const float4 a0 = *reinterpret_cast<const float4*>(s_c + row * 168 + c8 * 8);
                        const float4 a1 = *reinterpret_cast<const float4*>(s_c + row * 168 + c8 * 8 + 4);
                        const uint32_t o0 = badd(xv.x, bmul(gb.x, badd(pack_bf16(a0.x, a0.y), b22)));
                        const uint32_t o1 = badd(xv.y, bmul(gb.y, badd(pack_bf16(a0.z, a0.w), b22)));
                        const uint32_t o2 = badd(xv.z, bmul(gb.z, badd(pack_bf16(a1.x, a1.y), b22)));
                        const uint32_t o3 = badd(xv.w, bmul(gb.w, badd(pack_bf16(a1.z, a1.w), b22)));
                        stg128(p.out + (size_t)(mt * 64 + row) * D_ + nt * 160 + c8 * 8, o0, o1, o2, o3);
                    }
                }
            }
        }
        CLK(34 + g);
        TSTAMP(10 + 2 * g);
        if (g == 0) {
            asm volatile("fence.proxy.async.shared::cta;" ::: "memory");
            grid_arrive(4);
            DBG_STOP(4);
        }
    }
}

typedef CUresult (*EncodeFn)(CUtensorMap*, CUtensorMapDataType, cuuint32_t, void*, const cuuint64_t*, const cuuint64_t*,
                             const cuuint32_t*, const cuuint32_t*, CUtensorMapInterleave, CUtensorMapSwizzle,
                             CUtensorMapL2promotion, CUtensorMapFloatOOBfill);

CUtensorMap make_map(EncodeFn enc, void* ptr, int rank, const cuuint64_t* dims, const cuuint64_t* strides_bytes, const cuuint32_t* box,
                     CUtensorMapSwizzle swz = CU_TENSOR_MAP_SWIZZLE_128B) {
    CUtensorMap m;
    cuuint32_t es[3] = {1, 1, 1};
    enc(&m, CU_TENSOR_MAP_DATA_TYPE_BFLOAT16, rank, ptr, dims, strides_bytes, box, es, CU_TENSOR_MAP_INTERLEAVE_NONE,
        swz, CU_TENSOR_MAP_L2_PROMOTION_L2_128B, CU_TENSOR_MAP_FLOAT_OOB_FILL_NONE);
    return m;
}

}

extern "C" void kernel_launch(void* const* d_in, const int* in_sizes, int n_in, void* d_out, int out_size) {
    (void)in_sizes; (void)n_in; (void)out_size;
    static EncodeFn enc = nullptr;
    static void *p_h2 = nullptr, *p_u = nullptr;
    if (!enc) {
        void* fn = nullptr;
        cudaDriverEntryPointQueryResult qr;
        cudaGetDriverEntryPoint("cuTensorMapEncodeTiled", &fn, cudaEnableDefault, &qr);
        enc = (EncodeFn)fn;
        cudaGetSymbolAddress(&p_h2, g_h2);
        cudaGetSymbolAddress(&p_u, g_u);
        cudaFuncSetAttribute(fused_kernel, cudaFuncAttributeMaxDynamicSharedMemorySize, SM_TOTAL + 1024);
    }
    Params p;
    p.x = (const __nv_bfloat16*)d_in[0];
    p.w_r = (const __nv_bfloat16*)d_in[1];
    p.w_i = (const __nv_bfloat16*)d_in[2];
    p.w1 = (const __nv_bfloat16*)d_in[4];
    p.b1 = (const __nv_bfloat16*)d_in[5];
    p.w2 = (const __nv_bfloat16*)d_in[6];
    p.b2 = (const __nv_bfloat16*)d_in[7];
    p.c = (const __nv_bfloat16*)d_in[8];
    p.w_mod = (const __nv_bfloat16*)d_in[9];
    p.out = (__nv_bfloat16*)d_out;
    p.stop_after = 0;

    CUtensorMap tm_h2, tm_w1, tm_w2, tm_u, tm_wm, tm_x;
    {
        cuuint64_t dims[2] = {2048, 640}, str[1] = {H2P * 2};
        cuuint32_t box[2] = {64, 160};
        tm_h2 = make_map(enc, p_h2, 2, dims, str, box);
    }
    {
        cuuint64_t dims[3] = {1728, 16, 128}, str[2] = {(cuuint64_t)128 * 1728 * 2, 1728 * 2};
        cuuint32_t box[3] = {64, 16, 4};
        tm_w1 = make_map(enc, (void*)p.w1, 3, dims, str, box);
    }
    {
        cuuint64_t dims[2] = {2048, 1728}, str[1] = {2048 * 2};
        cuuint32_t box[2] = {64, 64};
        tm_w2 = make_map(enc, (void*)p.w2, 2, dims, str, box);
    }
    {
        cuuint64_t dims[2] = {1728, 640}, str[1] = {1728 * 2};
        cuuint32_t box[2] = {64, 160};
        tm_u = make_map(enc, p_u, 2, dims, str, box);
    }
    {
        cuuint64_t dims[2] = {3840, 640}, str[1] = {3840 * 2};
        cuuint32_t box[2] = {32, 128};
        tm_wm = make_map(enc, (void*)p.w_mod, 2, dims, str, box, CU_TENSOR_MAP_SWIZZLE_NONE);
    }
    {
        cuuint64_t dims[3] = {640, 16, 128}, str[2] = {(cuuint64_t)128 * 640 * 2, 640 * 2};
        cuuint32_t box[3] = {128, 16, 1};
        tm_x = make_map(enc, (void*)p.x, 3, dims, str, box, CU_TENSOR_MAP_SWIZZLE_NONE);
    }
    fused_kernel<<<NCTA, NT, SM_TOTAL + 1024, cudaStreamPerThread>>>(tm_h2, tm_w1, tm_w2, tm_u, tm_wm, tm_x, p);
}
```
